```python
import torch

def _softmax(x, axis=-1):
    return torch.softmax(x, dim=axis)
def _gelu(x):
    return torch.nn.functional.gelu(x, approximate="tanh")
def _silu(x):
    return torch.nn.functional.silu(x)
def _sigmoid(x):
    return torch.sigmoid(x)
def _layernorm(x, axis=-1, eps=1e-5):
    m = x.mean(dim=axis, keepdim=True)
    v = x.var(dim=axis, keepdim=True, unbiased=False)
    return (x - m) / torch.sqrt(v + eps)
def _scatter_add(tgt, idx, src, axis=0):
    return tgt.clone().index_add_(axis, idx, src)
def _segment_sum(src, seg, n):
    out = torch.zeros((n,) + src.shape[1:], dtype=src.dtype)
    return out.index_add_(0, seg, src)
def _pad(x, pw):
    flat = tuple(v for pair in reversed(pw) for v in pair)
    return torch.nn.functional.pad(x, flat)

kernel_name = 'parallel_sum__spectral_fnet__geglu_ffn__prompt'

def setup_inputs():

    _w = (lambda a: (lambda t: t.to(torch.bfloat16) if t.is_floating_point() else t)(torch.as_tensor(a)))
    def _A_setup():
        B, S, D = 1, 2048, 512
        ns = torch.arange(S)[:, None] * torch.arange(S)[None, :]
        nd = torch.arange(D)[:, None] * torch.arange(D)[None, :]
        Ws_re = torch.cos(-2.0 * torch.pi * ns / S).to(float)
        Ws_im = torch.sin(-2.0 * torch.pi * ns / S).to(float)
        Wd_re = torch.cos(-2.0 * torch.pi * nd / D).to(float)
        Wd_im = torch.sin(-2.0 * torch.pi * nd / D).to(float)
        return {
            "x": _w((lambda *s: torch.randn(*s, dtype=torch.bfloat16) * 0.05)(B, S, D)),
            "dft_seq_re": _w(Ws_re),
            "dft_seq_im": _w(Ws_im),
            "dft_hid_re": _w(Wd_re),
            "dft_hid_im": _w(Wd_im),
        }
    _A_in = _A_setup()

    def _B_setup():
        B, S, D, F = 1, 2048, 512, 1792
        return {
            "x": _w((lambda *s: torch.randn(*s, dtype=torch.bfloat16) * 0.05)(B, S, D)),
            "w_gate": _w((lambda *s: torch.randn(*s, dtype=torch.bfloat16) * 0.2)(D, F)),
            "w_up": _w((lambda *s: torch.randn(*s, dtype=torch.bfloat16) * 0.2)(D, F)),
            "w_down": _w((lambda *s: torch.randn(*s, dtype=torch.bfloat16) * 0.2)(F, D)),
        }
    _B_in = _B_setup()

    return {
        "A_x": _A_in["x"],
        "A_dft_seq_re": _A_in["dft_seq_re"],
        "A_dft_seq_im": _A_in["dft_seq_im"],
        "A_dft_hid_re": _A_in["dft_hid_re"],
        "A_dft_hid_im": _A_in["dft_hid_im"],
        "B_x": _B_in["x"],
        "B_w_gate": _B_in["w_gate"],
        "B_w_up": _B_in["w_up"],
        "B_w_down": _B_in["w_down"],
    }

def reference(A_x, A_dft_seq_re, A_dft_seq_im, A_dft_hid_re, A_dft_hid_im, B_x, B_w_gate, B_w_up, B_w_down):
    def _A_ref(x, dft_seq_re, dft_seq_im, dft_hid_re, dft_hid_im):
        a = torch.einsum("bsd,ed->bse", x, dft_hid_re)
        b = torch.einsum("bsd,ed->bse", x, dft_hid_im)
        y = torch.einsum("ts,bse->bte", dft_seq_re, a) - torch.einsum("ts,bse->bte", dft_seq_im, b)
        return y

    def _B_ref(x, w_gate, w_up, w_down):
        return (_gelu(x @ w_gate) * (x @ w_up)) @ w_down

    x = A_x
    xn = _layernorm(x, axis=-1)
    return x + _A_ref(xn, A_dft_seq_re, A_dft_seq_im, A_dft_hid_re, A_dft_hid_im) + _B_ref(xn, B_w_gate, B_w_up, B_w_down)
```

```cpp
#include <cuda_runtime.h>
#include <cuda_bf16.h>
#include <cuda.h>
#include <stdint.h>

namespace {

constexpr int S_ = 2048, D_ = 512, F_ = 1792;
constexpr int NAUX = 4;
constexpr int NCTA = 128 + NAUX;
constexpr int NBLK = 14;
constexpr int BSLOTS = 6;
constexpr int NSOLO = 6;
#define PFW_AT 0
#define WROW_DELAY 300
#define AUX_DELAY 2500
#define POLL_DELAY 400
#define AB_DEP 0
#define GU_DEP 1
#define PF_A 8
#define PF_B 18
#define PF_GAP 600
#define PROMO CU_TENSOR_MAP_L2_PROMOTION_L2_128B
constexpr int BLK = 128 * 64 * 2;
constexpr int BOX_BYTES = 64 * 64 * 2;
constexpr int OFF_CS = NBLK * BLK;
constexpr int OFF_BAR = OFF_CS + 5 * 512;
constexpr int SMEM_BYTES = OFF_BAR + 448;
constexpr int OFF_STAT = OFF_CS + 3 * 512;

constexpr int BAR_XFULL = 0, BAR_BFULL = 8, BAR_FULL = 14, BAR_CSRDY = 22, BAR_ABOK = 26, BAR_HOK = 27, BAR_EPOCH = 28,
              BAR_ABPOLL = 29, BAR_HPOLL = 30, BAR_XFREE = 31, BAR_PREP = 32,
              BAR_BEMPTY = 33, BAR_PUB = 39, BAR_ABST = 40,
              BAR_EMPTY = 41, BAR_DONE = 49, BAR_STATFREE = 50,
              BAR_HST = 51, NUM_BARS = 52;

constexpr int CNT_TICKET = 0, CNT_AB = 1, CNT_H = 2;
constexpr unsigned N_AB = 128, N_H = 8;

enum { M_X = 0, M_WR, M_WI, M_WG, M_WU, M_CR, M_CI, M_OUTI, M_AB, M_WD, M_H, M_OUT, NUM_MAPS };

struct Params {
    CUtensorMap m[NUM_MAPS];
    const __nv_bfloat16 *wr, *wi, *wg, *wu, *wd;
    uint32_t zero;
};

__device__ __align__(1024) __nv_bfloat16 g_AB[2 * S_ * D_];
__device__ __align__(1024) __nv_bfloat16 g_H[S_ * F_];
__device__ __align__(128) uint2 g_cs[2 * F_];
__device__ __align__(128) uint4 g_rs[2 * D_];
__device__ __align__(128) uint4 g_st[S_];
__device__ __align__(128) unsigned g_cnt[(CNT_H + 16) * 32];

#define TL(role, idx)
#define TLC(idx)

__device__ __forceinline__ uint32_t smem_u32(const void* p) { return (uint32_t)__cvta_generic_to_shared(p); }
__device__ __forceinline__ bool elect_one() {
    uint32_t r;
    asm volatile("{\n.reg .pred p;\nelect.sync _|p, 0xffffffff;\nselp.u32 %0, 1, 0, p;\n}" : "=r"(r));
    return r;
}
__device__ __forceinline__ void mbar_init(uint32_t bar, uint32_t cnt) {
    asm volatile("mbarrier.init.shared::cta.b64 [%0], %1;" ::"r"(bar), "r"(cnt) : "memory");
}
__device__ __forceinline__ void mbar_expect_tx(uint32_t bar, uint32_t bytes) {
    asm volatile("mbarrier.arrive.expect_tx.shared::cta.b64 _, [%0], %1;" ::"r"(bar), "r"(bytes) : "memory");
}
__device__ __forceinline__ void mbar_arrive(uint32_t bar) {
    asm volatile("mbarrier.arrive.shared::cta.b64 _, [%0];" ::"r"(bar) : "memory");
}
__device__ __forceinline__ void mbar_arrive_n(uint32_t bar, uint32_t n) {
    asm volatile("mbarrier.arrive.shared::cta.b64 _, [%0], %1;" ::"r"(bar), "r"(n) : "memory");
}
__device__ __forceinline__ bool mbar_try_wait(uint32_t bar, uint32_t parity) {
    uint32_t ok;
    asm volatile("{\n.reg .pred p;\nmbarrier.try_wait.parity.shared::cta.b64 p, [%1], %2;\nselp.u32 %0, 1, 0, p;\n}"
                 : "=r"(ok) : "r"(bar), "r"(parity) : "memory");
    return ok;
}
__device__ __forceinline__ void mbar_wait(uint32_t bar, uint32_t parity) {
    if (__builtin_expect(!mbar_try_wait(bar, parity), 0)) {
        int it = 0;
        while (!mbar_try_wait(bar, parity)) {
            if (++it > (1 << 20)) __trap();
        }
    }
}
__device__ __forceinline__ void tma_load_2d(uint32_t dst, const CUtensorMap* m, uint32_t bar, int c0, int c1) {
    asm volatile("cp.async.bulk.tensor.2d.shared::cluster.global.mbarrier::complete_tx::bytes [%0], [%1, {%3, %4}], [%2];"
                 ::"r"(dst), "l"(m), "r"(bar), "r"(c0), "r"(c1) : "memory");
}
__device__ __forceinline__ void tma_load_3d(uint32_t dst, const CUtensorMap* m, uint32_t bar, int c0, int c1, int c2) {
    asm volatile("cp.async.bulk.tensor.3d.shared::cluster.global.mbarrier::complete_tx::bytes [%0], [%1, {%3, %4, %5}], [%2];"
                 ::"r"(dst), "l"(m), "r"(bar), "r"(c0), "r"(c1), "r"(c2) : "memory");
}
__device__ __forceinline__ void tma_load_5d(uint32_t dst, const CUtensorMap* m, uint32_t bar, int c0, int c4) {
    asm volatile("cp.async.bulk.tensor.5d.shared::cluster.global.mbarrier::complete_tx::bytes [%0], [%1, {%3, %5, %5, %5, %4}], [%2];"
                 ::"r"(dst), "l"(m), "r"(bar), "r"(c0), "r"(c4), "r"(0) : "memory");
}
__device__ __forceinline__ void tma_store_2d(const CUtensorMap* m, uint32_t src, int c0, int c1) {
    asm volatile("cp.async.bulk.tensor.2d.global.shared::cta.bulk_group [%0, {%2, %3}], [%1];"
                 ::"l"(m), "r"(src), "r"(c0), "r"(c1) : "memory");
}
__device__ __forceinline__ void tma_red_add_2d(const CUtensorMap* m, uint32_t src, int c0, int c1) {
    asm volatile("cp.reduce.async.bulk.tensor.2d.global.shared::cta.add.tile.bulk_group [%0, {%2, %3}], [%1];"
                 ::"l"(m), "r"(src), "r"(c0), "r"(c1) : "memory");
}
__device__ __forceinline__ void tma_prefetch_2d(const CUtensorMap* m, int c0, int c1) {
    asm volatile("cp.async.bulk.prefetch.tensor.2d.L2.global [%0, {%1, %2}];" ::"l"(m), "r"(c0), "r"(c1) : "memory");
}
__device__ __forceinline__ void bulk_prefetch(const void* src, uint32_t bytes) {
    asm volatile("cp.async.bulk.prefetch.L2.global [%0], %1;" ::"l"(src), "r"(bytes) : "memory");
}
__device__ __forceinline__ void prefetch_map(const CUtensorMap* m) {
    asm volatile("prefetch.tensormap [%0];" ::"l"(m) : "memory");
}
__device__ __forceinline__ void bulk_commit() { asm volatile("cp.async.bulk.commit_group;" ::: "memory"); }
template <int N> __device__ __forceinline__ void bulk_wait() {
    asm volatile("cp.async.bulk.wait_group %0;" ::"n"(N) : "memory");
}
template <int N> __device__ __forceinline__ void bulk_wait_read() {
    asm volatile("cp.async.bulk.wait_group.read %0;" ::"n"(N) : "memory");
}
__device__ __forceinline__ void fence_async_smem() { asm volatile("fence.proxy.async.shared::cta;" ::: "memory"); }
__device__ __forceinline__ void fence_async_global() { asm volatile("fence.proxy.async.global;" ::: "memory"); }
__device__ __forceinline__ void wgmma_fence() { asm volatile("wgmma.fence.sync.aligned;" ::: "memory"); }
__device__ __forceinline__ void wgmma_commit() { asm volatile("wgmma.commit_group.sync.aligned;" ::: "memory"); }
template <int N> __device__ __forceinline__ void wgmma_wait() {
    asm volatile("wgmma.wait_group.sync.aligned %0;" ::"n"(N) : "memory");
}
__device__ __forceinline__ uint32_t make_desc(uint32_t addr, uint32_t lbo) { return (addr >> 4) | ((lbo >> 4) << 16); }
#define DESC_PRE(a, b) "{\n.reg .b64 da, db;\nmov.b64 da, {" a ", 0x40000040};\nmov.b64 db, {" b ", 0x40000040};\n"
__device__ __forceinline__ void red_release(unsigned* p) {
    asm volatile("red.release.gpu.global.add.u32 [%0], 1;" ::"l"(p) : "memory");
}
__device__ __forceinline__ void wait_counter(const unsigned* p, unsigned target) {
    int it = 0;
    while (true) {
        unsigned v;
        asm volatile("ld.acquire.gpu.global.u32 %0, [%1];" : "=r"(v) : "l"(p) : "memory");
        if ((int)(v - target) >= 0) break;
        if (++it > (1 << 17)) __trap();
        __nanosleep(40);
    }
}
__device__ __forceinline__ uint4 ldg_nc(const void* p) {
    uint4 v;
    asm volatile("ld.global.nc.L1::no_allocate.L2::256B.v4.u32 {%0,%1,%2,%3}, [%4];"
                 : "=r"(v.x), "=r"(v.y), "=r"(v.z), "=r"(v.w) : "l"(p));
    return v;
}
__device__ __forceinline__ uint4 lds128(uint32_t a) {
    uint4 v;
    asm volatile("ld.shared.v4.u32 {%0,%1,%2,%3}, [%4];" : "=r"(v.x), "=r"(v.y), "=r"(v.z), "=r"(v.w) : "r"(a) : "memory");
    return v;
}
__device__ __forceinline__ float4 lds128f(uint32_t a) {
    float4 v;
    asm volatile("ld.shared.v4.f32 {%0,%1,%2,%3}, [%4];" : "=f"(v.x), "=f"(v.y), "=f"(v.z), "=f"(v.w) : "r"(a) : "memory");
    return v;
}
__device__ __forceinline__ float2 lds64f(uint32_t a) {
    float2 v;
    asm volatile("ld.shared.v2.f32 {%0,%1}, [%2];" : "=f"(v.x), "=f"(v.y) : "r"(a) : "memory");
    return v;
}
__device__ __forceinline__ void stmatrix_x4(uint32_t a, uint32_t r0, uint32_t r1, uint32_t r2, uint32_t r3) {
    asm volatile("stmatrix.sync.aligned.m8n8.x4.shared.b16 [%0], {%1,%2,%3,%4};"
                 ::"r"(a), "r"(r0), "r"(r1), "r"(r2), "r"(r3) : "memory");
}
__device__ __forceinline__ uint32_t pack_bf16(float lo, float hi) {
    uint32_t r;
    asm("cvt.rn.bf16x2.f32 %0, %1, %2;" : "=r"(r) : "f"(hi), "f"(lo));
    return r;
}
__device__ __forceinline__ float tanh_fast(float x) {
    float y;
    asm("tanh.approx.f32 %0, %1;" : "=f"(y) : "f"(x));
    return y;
}
__device__ __forceinline__ float after(float v, float dep, uint32_t zero) {
    uint32_t r;
    asm("lop3.b32 %0, %1, %2, %3, 0xF8;" : "=r"(r) : "r"(__float_as_uint(v)), "r"(__float_as_uint(dep)), "r"(zero));
    return __uint_as_float(r);
}
__device__ __forceinline__ void turn_wait(int wg) { asm volatile("bar.sync %0, 256;" ::"r"(1 + wg) : "memory"); }
__device__ __forceinline__ void turn_give(int wg) { asm volatile("bar.arrive %0, 256;" ::"r"(1 + wg) : "memory"); }

#define OPS8(c, d, b) c(d[b]), c(d[b + 1]), c(d[b + 2]), c(d[b + 3]), c(d[b + 4]), c(d[b + 5]), c(d[b + 6]), c(d[b + 7])
#define OPS32(c, d, b) OPS8(c, d, b), OPS8(c, d, b + 8), OPS8(c, d, b + 16), OPS8(c, d, b + 24)
#define REGS64 \
    "{%0,%1,%2,%3,%4,%5,%6,%7,%8,%9,%10,%11,%12,%13,%14,%15,%16,%17,%18,%19,%20,%21,%22,%23,%24,%25,%26,%27,%28,%29,%30,%31," \
    "%32,%33,%34,%35,%36,%37,%38,%39,%40,%41,%42,%43,%44,%45,%46,%47,%48,%49,%50,%51,%52,%53,%54,%55,%56,%57,%58,%59,%60,%61,%62,%63}"

template <int TB, int ACC>
__device__ __forceinline__ void wgmma_n128(float (&d)[64], uint32_t da, uint32_t db) {
    if (ACC)
        asm volatile(DESC_PRE("%64", "%65") "wgmma.mma_async.sync.aligned.m64n128k16.f32.bf16.bf16 " REGS64 ", da, db, 1, 1, 1, 0, %66;\n}"
                     : OPS32("+f", d, 0), OPS32("+f", d, 32) : "r"(da), "r"(db), "n"(TB));
    else
        asm volatile(DESC_PRE("%64", "%65") "wgmma.mma_async.sync.aligned.m64n128k16.f32.bf16.bf16 " REGS64 ", da, db, 0, 1, 1, 0, %66;\n}"
                     : OPS32("=f", d, 0), OPS32("=f", d, 32) : "r"(da), "r"(db), "n"(TB));
}

template <int ACC>
__device__ __forceinline__ void wgmma_n8_ta(float (&d)[4], uint32_t da, uint64_t db) {
    if (ACC)
        asm volatile("{\n.reg .b64 da;\nmov.b64 da, {%4, 0x40000040};\n"
                     "wgmma.mma_async.sync.aligned.m64n8k16.f32.bf16.bf16 {%0,%1,%2,%3}, da, %5, 1, 1, 1, 1, 0;\n}"
                     : "+f"(d[0]), "+f"(d[1]), "+f"(d[2]), "+f"(d[3]) : "r"(da), "l"(db));
    else
        asm volatile("{\n.reg .b64 da;\nmov.b64 da, {%4, 0x40000040};\n"
                     "wgmma.mma_async.sync.aligned.m64n8k16.f32.bf16.bf16 {%0,%1,%2,%3}, da, %5, 0, 1, 1, 1, 0;\n}"
                     : "=f"(d[0]), "=f"(d[1]), "=f"(d[2]), "=f"(d[3]) : "r"(da), "l"(db));
}

template <int TB, int ACC>
__device__ __forceinline__ void mma_unit_half(float (&e)[2][64], uint32_t da, uint32_t db) {
    constexpr int BSTEP = TB ? 128 : 2;
    wgmma_fence();
    wgmma_n128<TB, ACC>(e[0], da, db);
    wgmma_n128<TB, ACC>(e[1], da + 512, db);
    wgmma_n128<TB, 1>(e[0], da + 2, db + BSTEP);
    wgmma_n128<TB, 1>(e[1], da + 514, db + BSTEP);
    wgmma_commit();
}

__device__ __forceinline__ constexpr int x_blk(int kb) { return kb < 3 ? kb : 2 * kb - 2; }
__device__ __forceinline__ constexpr int w_blk(int sl) { return 3 + 2 * sl; }

__device__ __forceinline__ void store_tagged(uint2* dst, float v, uint32_t tag) {
    asm volatile("st.relaxed.gpu.global.v2.u32 [%0], {%1, %2};" ::"l"(dst), "r"(__float_as_uint(v)), "r"(tag) : "memory");
}
__device__ __forceinline__ void store_tagged2(uint4* dst, float v0, float v1, uint32_t tag) {
    asm volatile("st.relaxed.gpu.global.v4.u32 [%0], {%1, %3, %2, %3};"
                 ::"l"(dst), "r"(__float_as_uint(v0)), "r"(__float_as_uint(v1)), "r"(tag) : "memory");
}
__device__ __forceinline__ uint4 ld_relaxed(const void* src) {
    uint4 v;
    asm volatile("ld.relaxed.gpu.global.v4.u32 {%0,%1,%2,%3}, [%4];"
                 : "=r"(v.x), "=r"(v.y), "=r"(v.z), "=r"(v.w) : "l"(src) : "memory");
    return v;
}
__device__ __forceinline__ float bf_lo(uint32_t u) { return __uint_as_float(u << 16); }
__device__ __forceinline__ float bf_hi(uint32_t u) { return __uint_as_float(u & 0xffff0000u); }
__device__ __forceinline__ uint32_t word(const uint4& v, int j) { return j == 0 ? v.x : (j == 1 ? v.y : (j == 2 ? v.z : v.w)); }

__device__ __forceinline__ void aux_column_sums(const Params& p, uint32_t base, int a, int warp, int lane) {
    constexpr int SLOT = 8 * BOX_BYTES;
    const uint32_t full = base + OFF_BAR, empty = full + 24, tag_addr = full + 48;
    const uint32_t t0 = clock();
    if (warp == 8) {
        if (elect_one()) {
#pragma unroll
            for (int i = 0; i < 3; i++) { mbar_init(full + 8 * i, 1); mbar_init(empty + 8 * i, 4); }
            asm volatile("fence.mbarrier_init.release.cluster;" ::: "memory");
            const uint32_t tag = atomicAdd(&g_cnt[CNT_TICKET], 1u) / NCTA + 1;
            asm volatile("st.shared.u32 [%0], %1;" ::"r"(tag_addr), "r"(tag) : "memory");
        }
    } else if (warp == 0 && lane < 16) {
        asm volatile("st.shared.v4.u32 [%0], {%1,%1,%1,%1};" ::"r"(base + OFF_CS + lane * 16), "r"(0x3F803F80u) : "memory");
        fence_async_smem();
    }
    __syncthreads();
    if (warp == 8) {
        if (elect_one()) {
            while ((uint32_t)clock() - t0 < AUX_DELAY) {}
            const CUtensorMap* m = &p.m[(a & 1) ? M_WU : M_WG];
#pragma unroll 1
            for (int j = 0; j < 14; j++) {
                const int sl = j % 3;
                if (j >= 3) mbar_wait(empty + 8 * sl, (j / 3 - 1) & 1);
                mbar_expect_tx(full + 8 * sl, SLOT);
#pragma unroll
                for (int kb = 0; kb < 8; kb++)
                    tma_load_2d(base + sl * SLOT + kb * BOX_BYTES, m, full + 8 * sl, (2 * j + (a >> 1)) * 64, kb * 64);
            }
        }
    } else if (warp < 4) {
        uint32_t tag;
        asm volatile("ld.shared.u32 %0, [%1];" : "=r"(tag) : "r"(tag_addr) : "memory");
        const uint64_t ones = (uint64_t)make_desc(base + OFF_CS, 128) | ((uint64_t)(256 >> 4) << 32);
#pragma unroll 1
        for (int j = 0; j < 14; j++) {
            const int sl = j % 3;
            const uint32_t da = make_desc(base + sl * SLOT, 8192);
            float d[4][4];
            mbar_wait(full + 8 * sl, (j / 3) & 1);
            wgmma_fence();
#pragma unroll
            for (int k = 0; k < 4; k++) wgmma_n8_ta<0>(d[k], da + k * 128, ones);
#pragma unroll
            for (int k = 4; k < 32; k++) wgmma_n8_ta<1>(d[k & 3], da + k * 128, ones);
            wgmma_commit();
            wgmma_wait<0>();
            if (lane == 0) mbar_arrive(empty + 8 * sl);
            if ((lane & 3) == 0) {
                uint2* dst = g_cs + (a & 1) * F_ + (2 * j + (a >> 1)) * 64 + warp * 16 + (lane >> 2);
                store_tagged(dst, (d[0][0] + d[1][0]) + (d[2][0] + d[3][0]), tag);
                store_tagged(dst + 8, (d[0][2] + d[1][2]) + (d[2][2] + d[3][2]), tag);
            }
            if (threadIdx.x == 0) TL(2, j);
        }
    }
}

template <int V> struct IntC { static constexpr int value = V; };

__global__ void __launch_bounds__(384, 1) fused_kernel(const __grid_constant__ Params p) {
    extern __shared__ __align__(1024) uint8_t smem_raw[];
    const uint32_t base = smem_u32(smem_raw);
    const uint32_t bars = base + OFF_BAR;
    auto bar = [&](int i) { return bars + 8 * i; };
    const uint32_t epoch_addr = bars + 8 * NUM_BARS;

    const int b = blockIdx.x - NAUX;
    const int nh = b & 1, rb = (b >> 1) & 15, ks = b >> 5;
    const int role = nh * 4 + ks;
    const int nunits = (ks >= 2) ? 5 : 4;
    const int ndft = (ks >= 2) ? 14 : 18;
    const int dft0 = (ks >= 2) ? 8 + ks * 14 : ks * 18;
    auto gu_chunk = [&](int u) { return u < 4 ? (u - 1) * 8 + role : 22 + nh * 2 + ks; };

    const int warp = __shfl_sync(0xffffffffu, threadIdx.x >> 5, 0), lane = threadIdx.x & 31;

    if (b < 0) {
        aux_column_sums(p, base, blockIdx.x, warp, lane);
        return;
    }

    const int boff = (nunits == 4) ? 4 : 2;
    const CUtensorMap* mab = &p.m[nh ? M_WI : M_WR];
    const int lead_wg = nunits & 1;
    const int nk = ndft + 7;

    if (threadIdx.x == 256) TL(2, 10);
    if (warp == 8) {
        const bool lead = elect_one();
        if (lead) {
#pragma unroll
            for (int i = 0; i < BAR_FULL; i++) mbar_init(bar(i), 1);
#pragma unroll
            for (int i = 0; i < 4; i++)
                if (i < boff) mbar_arrive(bar(BAR_BFULL + i));
            asm volatile("fence.mbarrier_init.release.cluster;" ::: "memory");
        }
        asm volatile("bar.arrive 4, 384;" ::: "memory");
        if (lead) {
            TL(2, 0);
            int sl = boff;
#pragma unroll
            for (int kb = 0; kb < 8; kb++) {
                mbar_expect_tx(bar(BAR_XFULL + kb), BLK);
                tma_load_2d(base + x_blk(kb) * BLK, &p.m[M_X], bar(BAR_XFULL + kb), kb * 64, rb * 128);
                if (kb < BSLOTS) {
                    mbar_expect_tx(bar(BAR_BFULL + sl), BLK);
                    tma_load_5d(base + w_blk(sl) * BLK, mab, bar(BAR_BFULL + sl), kb * 64, ks * 4);
                    if (++sl == BSLOTS) sl = 0;
                }
            }
            TL(2, 6);
        }
        asm volatile("bar.sync 5, 64;" ::: "memory");
    } else {
        if (warp == 0) {
            if (elect_one()) {
                if (base & 1023) __trap();
#pragma unroll
                for (int i = BAR_FULL; i < BAR_HST; i++) mbar_init(bar(i), i < BAR_BEMPTY ? 1 : (i < BAR_EMPTY ? 4 : 8));
                mbar_init(bar(BAR_HST), 4 * (nunits - 1));
#pragma unroll
                for (int i = 0; i < 4; i++)
                    if (i < boff) mbar_arrive_n(bar(BAR_BEMPTY + i), 4);
                asm volatile("fence.mbarrier_init.release.cluster;" ::: "memory");
            }
            asm volatile("bar.arrive 5, 64;" ::: "memory");
        }
        asm volatile("bar.sync 4, 384;" ::: "memory");
    }

    if (warp >= 8) {
        if (warp == 8) {
            if (elect_one()) {
                int ls = boff;
                uint32_t ph = 0;
                uint32_t fb, sb;
                auto next_slot = [&]() {
                    mbar_wait(bar(BAR_BEMPTY + ls), ph);
                    fb = bar(BAR_BFULL + ls);
                    sb = base + w_blk(ls) * BLK;
                    mbar_expect_tx(fb, BLK);
                    if (++ls == BSLOTS) { ls = 0; ph ^= 1; }
                };
#pragma unroll
                for (int kb = BSLOTS; kb < 8; kb++) {
                    next_slot();
                    tma_load_5d(sb, mab, fb, kb * 64, ks * 4);
                }
#pragma unroll 1
                for (int u = 1; u < nunits; u++) {
                    const int c = gu_chunk(u) * 64;
#pragma unroll 1
                    for (int k = 0; k < D_; k += 64) {
                        next_slot();
                        tma_load_2d(sb, &p.m[M_WG], fb, c, k);
                        tma_load_2d(sb + BOX_BYTES, &p.m[M_WU], fb, c, k);
                    }
                }
                TL(2, 1);
                mbar_wait(bar(BAR_XFREE), 0);
                mbar_wait(bar(BAR_ABOK), 0);
                fence_async_global();
                TL(2, 2);
                static_assert(NSOLO == 6 && NBLK == 14, "the wait schedule below is written for this ring");
                const CUtensorMap* mc = &p.m[dft0 < 32 ? M_CR : M_CI];
                const int cl = nh * 4 + 2 * lead_wg, cf = nh * 4 + 2 * (lead_wg ^ 1), arow = rb * 128;
                auto wait_step = [&](int t) { mbar_wait(bar(BAR_EMPTY + (t & 7)), (t >> 3) & 1); };
                auto blk = [&](int i) { return base + (i >= NBLK ? i - NBLK : i) * BLK; };
#pragma unroll
                for (int s = 0; s < 11; s++) {
                    const int k = (dft0 + s) * 64;
                    const int pos = s < NSOLO ? 2 * s : (3 * s - NSOLO) % NBLK;
                    fb = bar(BAR_FULL + (s & 7));
                    if (s >= 1 && s <= 6) mbar_wait(bar(BAR_BEMPTY + s - 1), ph);
                    if (s == 8) wait_step(2);
                    if (s == 10) wait_step(5);
                    mbar_expect_tx(fb, s < NSOLO ? 2 * BLK : 3 * BLK);
                    tma_load_2d(blk(pos), mc, fb, k & (S_ - 1), arow);
                    if (s == 7) wait_step(1);
                    if (s == 9) wait_step(4);
                    tma_load_3d(blk(pos + 1), &p.m[M_AB], fb, 0, k, s < NSOLO ? cl : cf);
                    if (s >= NSOLO) {
                        if (s == 6) wait_step(0);
                        if (s == 8) wait_step(3);
                        if (s == 10) wait_step(6);
                        tma_load_3d(blk(pos + 2), &p.m[M_AB], fb, 0, k, cl);
                    }
                    TL(2, 32 + s);
                }
                mbar_arrive(bar(BAR_HPOLL));
                int pos = (33 - NSOLO) % NBLK;
#pragma unroll 1
                for (int s = 11; s < ndft; s++) {
                    const int k = (dft0 + s) * 64;
                    fb = bar(BAR_FULL + (s & 7));
                    mbar_expect_tx(fb, 3 * BLK);
                    tma_load_2d(blk(pos), &p.m[k < S_ ? M_CR : M_CI], fb, k & (S_ - 1), arow);
                    tma_load_3d(blk(pos + 1), &p.m[M_AB], fb, 0, k, cf);
                    wait_step(s - 4);
                    tma_load_3d(blk(pos + 2), &p.m[M_AB], fb, 0, k, cl);
                    if (s < 14) TL(2, 32 + s);
                    pos += 3;
                    if (pos >= NBLK) pos -= NBLK;
                }
                TL(2, 3);
                mbar_wait(bar(BAR_HOK), 0);
                fence_async_global();
                TL(2, 4);
#pragma unroll 1
                for (int s = ndft; s < nk; s++) {
                    const int kb = ks * 7 + s - ndft;
                    fb = bar(BAR_FULL + (s & 7));
                    mbar_expect_tx(fb, 3 * BLK);
                    tma_load_2d(blk(pos), &p.m[M_H], fb, kb * 64, arow);
                    tma_load_5d(blk(pos + 1), &p.m[M_WD], fb, cf * 64, kb * 2);
                    tma_load_5d(blk(pos + 1) + BOX_BYTES, &p.m[M_WD], fb, cf * 64 + 64, kb * 2);
                    wait_step(s - 4);
                    tma_load_5d(blk(pos + 2), &p.m[M_WD], fb, cl * 64, kb * 2);
                    tma_load_5d(blk(pos + 2) + BOX_BYTES, &p.m[M_WD], fb, cl * 64 + 64, kb * 2);
                    pos += 3;
                    if (pos >= NBLK) pos -= NBLK;
                }
#pragma unroll
                for (int j = 0; j < NSOLO; j++) {
                    const int k = (dft0 + j) * 64;
                    fb = bar(BAR_FULL + ((nk + j) & 7));
                    if (j == 1) wait_step(nk - 4);
                    if (j == 4) wait_step(nk - 2);
                    mbar_expect_tx(fb, 2 * BLK);
                    tma_load_2d(blk(pos), mc, fb, k & (S_ - 1), arow);
                    if (j == 2) wait_step(nk - 3);
                    if (j == 5) wait_step(nk - 1);
                    tma_load_3d(blk(pos + 1), &p.m[M_AB], fb, 0, k, cf);
                    pos += 2;
                    if (pos >= NBLK) pos -= NBLK;
                }
                TL(2, 5);
            }
        } else {
            const int w = warp - 9;
            uint32_t tag;
            if (w == 1 && lane == 0) {
                tag = atomicAdd(&g_cnt[CNT_TICKET], 1u) / NCTA + 1;
                asm volatile("st.shared.u32 [%0], %1;" ::"r"(epoch_addr), "r"(tag) : "memory");
                mbar_arrive(bar(BAR_EPOCH));
            }
            if (w == 2 && elect_one()) {
                mbar_wait(bar(BAR_XFULL + PFW_AT), 0);
                bulk_prefetch((b < 64 ? p.wg : p.wu) + (size_t)(b & 63) * 8 * F_, 8 * F_ * 2);
            }
            __syncwarp();
            mbar_wait(bar(BAR_EPOCH), 0);
            asm volatile("ld.shared.u32 %0, [%1];" : "=r"(tag) : "r"(epoch_addr) : "memory");
            if (w == 0) {
                if (elect_one()) {
                    auto prefetch_dft = [&](int i0, int i1) {
#pragma unroll 1
                        for (int i = i0 + nh; i < i1; i += 2) {
                            const int kb = dft0 + i;
                            tma_prefetch_2d(&p.m[kb < 32 ? M_CR : M_CI], (kb & 31) * 64, rb * 128);
                            __nanosleep(PF_GAP);
                        }
                    };
                    mbar_wait(bar(BAR_XFULL), 0);
                    prefetch_map(&p.m[M_WG]);
                    prefetch_map(&p.m[M_WU]);
                    mbar_wait(bar(BAR_PREP), 0);
#pragma unroll 1
                    for (int i = M_CR; i < NUM_MAPS; i++) prefetch_map(&p.m[i]);
                    prefetch_dft(0, PF_A);
                    mbar_wait(bar(BAR_ABPOLL), 0);
                    wait_counter(&g_cnt[CNT_AB], tag * N_AB);
                    mbar_arrive(bar(BAR_ABOK));
                    TL(2, 26);
                    prefetch_dft(PF_A, PF_B < ndft ? PF_B : ndft);
                    bulk_prefetch(p.wd + (size_t)b * 14 * D_, 14 * D_ * 2);
                    mbar_wait(bar(BAR_HPOLL), 0);
                    wait_counter(&g_cnt[(CNT_H + rb) * 32], tag * N_H);
                    mbar_arrive(bar(BAR_HOK));
                    TL(2, 27);
                    mbar_wait(bar(BAR_DONE), 0);
                }
            } else if (w == 1) {
                mbar_wait(bar(BAR_PUB), 0);
                __nanosleep(POLL_DELAY);
                uint4 v[6];
                int it = 0;
                while (true) {
#pragma unroll
                    for (int i = 0; i < 4; i++) v[i] = ld_relaxed(g_st + rb * 128 + i * 32 + lane);
#pragma unroll
                    for (int i = 0; i < 2; i++) v[4 + i] = ld_relaxed(g_rs + role * 128 + lane * 4 + i * 2);
                    bool ok = true;
#pragma unroll
                    for (int i = 0; i < 6; i++) ok = ok && v[i].y == tag && v[i].w == tag;
                    if (__all_sync(0xffffffffu, ok)) break;
                    if (++it > (1 << 16)) __trap();
                }
#pragma unroll
                for (int i = 0; i < 4; i++)
                    asm volatile("st.shared.v2.u32 [%0], {%1,%2};" ::"r"(base + OFF_STAT + (i * 32 + lane) * 8), "r"(v[i].x), "r"(v[i].z) : "memory");
                asm volatile("st.shared.v4.u32 [%0], {%1,%2,%3,%4};"
                             ::"r"(base + OFF_CS + lane * 16), "r"(v[4].x), "r"(v[4].z), "r"(v[5].x), "r"(v[5].z) : "memory");
                __syncwarp();
                if (elect_one()) {
                    mbar_arrive(bar(BAR_PREP));
                    TL(2, 8);
                    mbar_wait(bar(BAR_ABST), 0);
                    TL(2, 24);
                    red_release(&g_cnt[CNT_AB]);
                    mbar_arrive(bar(BAR_ABPOLL));
                    TL(2, 12);
                    const uint32_t xsrc = base + (role < 3 ? role : 2 * role - 2) * BLK;
                    tma_store_2d(&p.m[M_OUTI], xsrc, role * 64, rb * 128);
                    __nanosleep(500);
                    tma_store_2d(&p.m[M_OUTI], xsrc + BOX_BYTES, role * 64, rb * 128 + 64);
                    bulk_commit();
                    bulk_wait<0>();
                    mbar_arrive(bar(BAR_XFREE));
                    mbar_wait(bar(BAR_HST), 0);
                    red_release(&g_cnt[(CNT_H + rb) * 32]);
                    TL(2, 29);
                }
            } else {
                mbar_wait(bar(BAR_PREP), 0);
#pragma unroll 1
                for (int u = 1; u < nunits; u++) {
                    if (u == 3) mbar_wait(bar(BAR_STATFREE), 0);
                    const uint2* s0 = g_cs + gu_chunk(u) * 64 + lane * 2;
                    uint4 vg, vu;
                    int it = 0;
                    while (true) {
                        vg = ld_relaxed(s0);
                        vu = ld_relaxed(s0 + F_);
                        if (__all_sync(0xffffffffu, vg.y == tag && vg.w == tag && vu.y == tag && vu.w == tag)) break;
                        if (++it > (1 << 16)) __trap();
                        __nanosleep(200);
                    }
                    asm volatile("st.shared.v4.u32 [%0], {%1,%2,%3,%4};"
                                 ::"r"(base + OFF_CS + u * 512 + lane * 16), "r"(vg.x), "r"(vg.z), "r"(vu.x), "r"(vu.z) : "memory");
                    __syncwarp();
                    if (lane == 0) { mbar_arrive(bar(BAR_CSRDY + u - 1)); TL(2, 18 + u); }
                }
            }
        }
    } else {
        const int wg = warp >> 2, wq = warp & 3;
        const int q = lane & 3;
        float nm[4], rs[4];
        auto load_stats = [&]() {
            mbar_wait(bar(BAR_PREP), 0);
#pragma unroll
            for (int i = 0; i < 4; i++) {
                const float2 v = lds64f(base + OFF_STAT + ((i >> 1) * 64 + wq * 16 + (i & 1) * 8 + (lane >> 2)) * 8);
                nm[i] = v.x;
                rs[i] = v.y;
            }
            __syncwarp();
            if (lane == 0) mbar_arrive(bar(BAR_STATFREE));
        };
        if (wg == 1) {
            turn_give(0);
            const int row0 = rb * 128 + role * 16 + wq * 4;
            const int wrow0 = role * 128 + rb * 8 + wq * 2;
            const __nv_bfloat16* ws = (nh ? p.wi : p.wr) + (size_t)((wrow0 & 511) + (lane >> 4)) * D_ + (lane & 15) * 8;
            const uint32_t xs = base + (role * 16 + wq * 4) * 128 + lane * 16;
            uint4 wv[4];
            const uint32_t t0 = clock();
            while ((uint32_t)clock() - t0 < WROW_DELAY) {}
#pragma unroll
            for (int i = 0; i < 4; i++) wv[i] = ldg_nc(ws + i * 128);
            float wsv = 0.f;
#pragma unroll
            for (int i = 0; i < 16; i++) wsv = (wsv + bf_lo(word(wv[i >> 2], i & 3))) + bf_hi(word(wv[i >> 2], i & 3));
#pragma unroll
            for (int o = 1; o < 16; o <<= 1) wsv += __shfl_xor_sync(0xffffffffu, wsv, o);
            const float wso = __shfl_xor_sync(0xffffffffu, wsv, 16);
            uint32_t tag;
            mbar_wait(bar(BAR_EPOCH), 0);
            asm volatile("ld.shared.u32 %0, [%1];" : "=r"(tag) : "r"(epoch_addr) : "memory");
            if (lane < 2) store_tagged2(g_rs + wrow0 + lane, wsv, wso, tag);
            float s1 = 0.f, s2 = 0.f;
#pragma unroll
            for (int kb = 0; kb < 8; kb++) {
                mbar_wait(bar(BAR_XFULL + kb), 0);
                const uint4 xv = lds128(xs + x_blk(kb) * BLK);
#pragma unroll
                for (int i = 0; i < 4; i++) {
                    const float lo = bf_lo(word(xv, i)), hi = bf_hi(word(xv, i));
                    s1 = (s1 + lo) + hi;
                    s2 = fmaf(hi, hi, fmaf(lo, lo, s2));
                }
            }
            TLC(57);
#pragma unroll
            for (int o = 1; o < 8; o <<= 1) {
                s1 += __shfl_xor_sync(0xffffffffu, s1, o);
                s2 += __shfl_xor_sync(0xffffffffu, s2, o);
            }
            const float mean = s1 * (1.f / D_);
            const float rsv = rsqrtf(fmaxf(fmaf(-mean, mean, s2 * (1.f / D_)), 0.f) + 1e-5f);
            if ((lane & 7) == 0) store_tagged2(g_st + row0 + (lane >> 3), -mean, rsv, tag);
            __syncwarp();
            if (lane == 0) mbar_arrive(bar(BAR_PUB));
            TLC(58);
        }

        auto run_unit = [&](auto tb, float (&e)[2][64], int u) {
            constexpr int TB = decltype(tb)::value;
            constexpr int BSTEP = TB ? 128 : 2;
            const uint32_t da = make_desc(base, 16);
            const uint32_t db0 = make_desc(base + w_blk(0) * BLK, TB ? 8192 : 16);
            int sl = (u * 8 + boff) % BSLOTS, prev = 0;
            uint32_t ph = ((u * 8 + boff) / BSLOTS) & 1;
            turn_wait(wg);
#pragma unroll
            for (int kb = 0; kb < 8; kb++) {
                const uint32_t db = db0 + sl * (2 * BLK >> 4);
                if (TB == 0) mbar_wait(bar(BAR_XFULL + kb), 0);
                mbar_wait(bar(BAR_BFULL + sl), ph);
                if (kb == 0) {
                    TLC((u >> 1) * 2);
                    mma_unit_half<TB, 0>(e, da, db);
                } else {
                    mma_unit_half<TB, 1>(e, da + x_blk(kb) * (BLK >> 4), db);
                    wgmma_wait<1>();
                    if (lane == 0) mbar_arrive(bar(BAR_BEMPTY + prev));
                }
                mma_unit_half<TB, 1>(e, da + x_blk(kb) * (BLK >> 4) + 4, db + 2 * BSTEP);
                prev = sl;
                if (++sl == BSLOTS) { sl = 0; ph ^= 1; }
            }
            turn_give(wg ^ 1);
            wgmma_wait<0>();
            if (lane == 0) mbar_arrive(bar(BAR_BEMPTY + prev));
            TLC(40 + (u >> 1) * 3);
        };

        const int trow = rb * 128 + wq * 16 + (lane >> 2);
        if (wg == 0) {
            float e[2][64];
            run_unit(IntC<0>(), e, 0);
            load_stats();
            TLC(41);
            const uint32_t csb = base + OFF_CS + q * 32;
            __nv_bfloat16* dst = g_AB + (size_t)(nh * S_ + trow) * D_ + ks * 128 + q * 8;
            const float sg = nh ? -1.f : 1.f;
            float dep = 0.f;
#pragma unroll
            for (int j = 0; j < 4; j++) {
                const float4 c0 = lds128f(csb + j * 128), c1 = lds128f(csb + j * 128 + 16);
                const float c[8] = {c0.x, c0.y, c0.z, c0.w, c1.x, c1.y, c1.z, c1.w};
#pragma unroll
                for (int mr = 0; mr < 4; mr++) {
                    const float r = rs[mr] * sg;
                    uint32_t o[4];
#pragma unroll
                    for (int i = 0; i < 4; i++) {
                        const float* v = e[mr >> 1] + 16 * j + 4 * i + 2 * (mr & 1);
                        const float n = AB_DEP == 2 ? nm[mr] : after(nm[mr], dep, p.zero);
                        const float t0 = fmaf(n, c[2 * i], v[0]);
                        const float v0 = t0 * r, v1 = fmaf(n, c[2 * i + 1], v[1]) * r;
                        o[i] = pack_bf16(v0, v1);
                        dep = AB_DEP == 0 ? v1 : (AB_DEP == 1 ? t0 : v0);
                    }
                    *reinterpret_cast<uint4*>(dst + ((mr >> 1) * 64 + (mr & 1) * 8) * D_ + j * 32) = make_uint4(o[0], o[1], o[2], o[3]);
                }
            }
            __syncwarp();
            if (lane == 0) mbar_arrive(bar(BAR_ABST));
            TLC(42);
        }
#pragma unroll 1
        for (int u = 2 - wg; u < nunits; u += 2) {
            float e[2][64];
            run_unit(IntC<1>(), e, u);
            if (u == 1) load_stats();
            mbar_wait(bar(BAR_CSRDY + u - 1), 0);
            TLC(41 + (u >> 1) * 3);
            const uint32_t csb = base + OFF_CS + u * 512 + q * 16;
            __nv_bfloat16* dst = g_H + (size_t)trow * F_ + gu_chunk(u) * 64 + q * 8;
            const float k0 = 0.7978845608028654f, k1 = 0.7978845608028654f * 0.044715f;
            float dep = 0.f;
#pragma unroll
            for (int mj = 0; mj < 4; mj++) {
                const int m = mj >> 1, j = mj & 1;
                uint32_t o[2][4];
#pragma unroll
                for (int i = 0; i < 4; i++) {
                    const float4 c = lds128f(csb + (4 * j + i) * 64);
#pragma unroll
                    for (int rr = 0; rr < 2; rr++) {
                        const float r = rs[2 * m + rr];
                        const float c0 = k0 * r, c1 = k1 * r * r * r, ch = 0.5f * r * r;
                        float hv[2];
#pragma unroll
                        for (int t = 0; t < 2; t++) {
                            const float* v = e[m] + 16 * j + 4 * i + 2 * rr + t;
                            const float n = GU_DEP == 3 ? nm[2 * m + rr] : after(nm[2 * m + rr], dep, p.zero);
                            const float tg = fmaf(n, t ? c.y : c.x, v[0]);
                            const float tu = fmaf(n, t ? c.w : c.z, v[32]);
                            const float sq = tg * tg, pl = fmaf(sq, c1, c0), z = tg * pl;
                            const float wv = (tg * ch) * tu;
                            hv[t] = fmaf(wv, tanh_fast(z), wv);
                            dep = GU_DEP == 0 ? z : (GU_DEP == 1 ? pl : sq);
                        }
                        o[rr][i] = pack_bf16(hv[0], hv[1]);
                    }
                }
#pragma unroll
                for (int rr = 0; rr < 2; rr++)
                    *reinterpret_cast<uint4*>(dst + (m * 64 + rr * 8) * F_ + j * 32) = make_uint4(o[rr][0], o[rr][1], o[rr][2], o[rr][3]);
            }
            __syncwarp();
            if (lane == 0) mbar_arrive(bar(BAR_HST));
            TLC(42 + (u >> 1) * 3);
        }

        const bool leader = wg == lead_wg;
        float e[2][64];
        const uint32_t da0 = make_desc(base, 16), db0 = make_desc(base, 8192);
        int s = leader ? 0 : NSOLO, pos = leader ? 0 : 2 * NSOLO;
        int spare = 0;
        uint32_t prev_bar = 0, prev_n = 0;
        auto step = [&](auto acc) {
            const bool shared = s >= NSOLO && s < nk;
            int pb = pos + ((shared && leader) ? 2 : 1);
            if (pb >= NBLK) pb -= NBLK;
            const uint32_t da = da0 + pos * (BLK >> 4), db = db0 + pb * (BLK >> 4);
            mbar_wait(bar(BAR_FULL + (s & 7)), (s >> 3) & 1);
            TLC(8 + s - (leader ? 0 : NSOLO));
            mma_unit_half<1, decltype(acc)::value>(e, da, db);
            if (decltype(acc)::value) {
                wgmma_wait<1>();
                if (lane == 0) mbar_arrive_n(prev_bar, prev_n);
            }
            mma_unit_half<1, 1>(e, da + 4, db + 256);
            prev_bar = bar(BAR_EMPTY + (s & 7));
            prev_n = shared ? 1 : 2;
            if (s == (leader ? nk - 1 : nk)) spare = leader ? pos + 1 : pos;
            pos += shared ? 3 : 2;
            if (pos >= NBLK) pos -= NBLK;
            s++;
        };
        if (leader) turn_wait(wg);
        step(IntC<0>());
#pragma unroll 1
        for (int i = 1; i < nk; i++) step(IntC<1>());
        wgmma_wait<0>();
        if (lane == 0) mbar_arrive_n(prev_bar, prev_n);
        TLC(50);
        {
            const int sd = leader ? nk - 1 : nk;
            mbar_wait(bar(BAR_EMPTY + (sd & 7)), (sd >> 3) & 1);
        }
        const uint32_t st_off = (wq * 16 + ((lane >> 3) & 1) * 8 + (lane & 7)) * 128;
        const uint32_t st_x = (lane >> 4), st_sw = lane & 7;
        const bool issuer = elect_one();
#pragma unroll
        for (int bx = 0; bx < 4; bx++) {
            const int m = bx >> 1, h = bx & 1;
            int blk = spare + m;
            if (blk >= NBLK) blk -= NBLK;
            const uint32_t box = base + blk * BLK + h * BOX_BYTES;
#pragma unroll
            for (int pr = 0; pr < 4; pr++) {
                const float* v = e[m] + h * 32 + pr * 8;
                stmatrix_x4(box + st_off + (((pr * 2 + st_x) ^ st_sw) << 4), pack_bf16(v[0], v[1]), pack_bf16(v[2], v[3]),
                            pack_bf16(v[4], v[5]), pack_bf16(v[6], v[7]));
            }
            fence_async_smem();
            __syncwarp();
            if (issuer) tma_red_add_2d(&p.m[M_OUT], box + wq * 2048, nh * 256 + wg * 128 + h * 64, rb * 128 + m * 64 + wq * 16);
        }
        if (issuer) {
            bulk_commit();
            TLC(51);
            bulk_wait_read<0>();
            TLC(52);
            mbar_arrive(bar(BAR_DONE));
        }
    }
}

typedef CUresult (*EncodeFn)(CUtensorMap*, CUtensorMapDataType, cuuint32_t, void*, const cuuint64_t*, const cuuint64_t*,
                             const cuuint32_t*, const cuuint32_t*, CUtensorMapInterleave, CUtensorMapSwizzle,
                             CUtensorMapL2promotion, CUtensorMapFloatOOBfill);

void map_2d(EncodeFn enc, CUtensorMap* m, const void* ptr, uint64_t rows, uint64_t cols, uint32_t box_rows) {
    cuuint64_t dims[2] = {cols, rows};
    cuuint64_t strides[1] = {cols * 2};
    cuuint32_t box[2] = {64, box_rows};
    cuuint32_t es[2] = {1, 1};
    enc(m, CU_TENSOR_MAP_DATA_TYPE_BFLOAT16, 2, const_cast<void*>(ptr), dims, strides, box, es, CU_TENSOR_MAP_INTERLEAVE_NONE,
        CU_TENSOR_MAP_SWIZZLE_128B, PROMO, CU_TENSOR_MAP_FLOAT_OOB_FILL_NONE);
}

void map_3d(EncodeFn enc, CUtensorMap* m, const void* ptr, uint64_t rows, uint64_t cols, uint32_t nchunk) {
    cuuint64_t dims[3] = {64, rows, cols / 64};
    cuuint64_t strides[2] = {cols * 2, 128};
    cuuint32_t box[3] = {64, 64, nchunk};
    cuuint32_t es[3] = {1, 1, 1};
    enc(m, CU_TENSOR_MAP_DATA_TYPE_BFLOAT16, 3, const_cast<void*>(ptr), dims, strides, box, es, CU_TENSOR_MAP_INTERLEAVE_NONE,
        CU_TENSOR_MAP_SWIZZLE_128B, PROMO, CU_TENSOR_MAP_FLOAT_OOB_FILL_NONE);
}

void map_5d(EncodeFn enc, CUtensorMap* m, const void* ptr, uint64_t rows, uint64_t sa, uint64_t sb, uint32_t ngroups) {
    const cuuint64_t pitch = D_ * 2;
    cuuint64_t dims[5] = {D_, 2, 4, 4, rows / 32};
    cuuint64_t strides[4] = {pitch, sa * pitch, sb * pitch, 32 * pitch};
    cuuint32_t box[5] = {64, 2, 4, 4, ngroups};
    cuuint32_t es[5] = {1, 1, 1, 1, 1};
    enc(m, CU_TENSOR_MAP_DATA_TYPE_BFLOAT16, 5, const_cast<void*>(ptr), dims, strides, box, es, CU_TENSOR_MAP_INTERLEAVE_NONE,
        CU_TENSOR_MAP_SWIZZLE_128B, PROMO, CU_TENSOR_MAP_FLOAT_OOB_FILL_NONE);
}

}

extern "C" void kernel_launch(void* const* d_in, const int* in_sizes, int n_in, void* d_out, int out_size) {
    (void)in_sizes; (void)n_in; (void)out_size;
    void* fn = nullptr;
    cudaDriverEntryPointQueryResult qr;
    cudaGetDriverEntryPoint("cuTensorMapEncodeTiled", &fn, cudaEnableDefault, &qr);
    EncodeFn enc = (EncodeFn)fn;
    void *ab = nullptr, *h = nullptr;
    cudaGetSymbolAddress(&ab, g_AB);
    cudaGetSymbolAddress(&h, g_H);

    Params p;
    p.wr = (const __nv_bfloat16*)d_in[3];
    p.wi = (const __nv_bfloat16*)d_in[4];
    p.wg = (const __nv_bfloat16*)d_in[6];
    p.wu = (const __nv_bfloat16*)d_in[7];
    p.wd = (const __nv_bfloat16*)d_in[8];
    p.zero = 0;
    map_2d(enc, &p.m[M_X], d_in[0], S_, D_, 128);
    map_5d(enc, &p.m[M_WR], d_in[3], D_, 8, 2, 4);
    map_5d(enc, &p.m[M_WI], d_in[4], D_, 8, 2, 4);
    map_2d(enc, &p.m[M_WG], d_in[6], D_, F_, 64);
    map_2d(enc, &p.m[M_WU], d_in[7], D_, F_, 64);
    map_2d(enc, &p.m[M_CR], d_in[1], S_, S_, 128);
    map_2d(enc, &p.m[M_CI], d_in[2], S_, S_, 128);
    map_3d(enc, &p.m[M_AB], ab, 2 * S_, D_, 2);
    map_5d(enc, &p.m[M_WD], d_in[8], F_, 8, 2, 2);
    map_2d(enc, &p.m[M_H], h, S_, F_, 128);
    map_2d(enc, &p.m[M_OUTI], d_out, S_, D_, 64);
    map_2d(enc, &p.m[M_OUT], d_out, S_, D_, 16);

    cudaFuncSetAttribute(fused_kernel, cudaFuncAttributeMaxDynamicSharedMemorySize, SMEM_BYTES);
    fused_kernel<<<NCTA, 384, SMEM_BYTES, cudaStreamPerThread>>>(p);
}
```

```cpp
#include <cuda_runtime.h>
#include <cuda_bf16.h>
#include <cuda.h>
#include <stdint.h>

namespace {

constexpr int S_ = 2048, D_ = 512, F_ = 1792;
constexpr int NAUX = 4;
constexpr int NCTA = 128 + NAUX;
constexpr int NBLK = 14;
constexpr int BSLOTS = 6;
#define NSOLO_ 7
constexpr int NSOLO = NSOLO_;
#define NSPLIT 4
#define PFW_AT 2
#define CS_SLEEP 100
#define AUX_WGS 2
#define AUX_DELAY 2500
#define POLL_DELAY 400
#define AB_DEP 1
#define GU_DEP 2
#define EARLY_GAP 350u
#define FAST_FIRST 1
#define EARLY_PF 1
#define PF_A 8
#define PF_B 18
#define PF_GAP 600
#define PROMO CU_TENSOR_MAP_L2_PROMOTION_L2_128B
#define SCALE_EXP 12
constexpr float SCALE_DOWN = 1.f / (float)(1u << SCALE_EXP);
constexpr uint32_t SCALE_UP2 = ((127u + SCALE_EXP) << 7) * 0x10001u;
constexpr int BLK = 128 * 64 * 2;
constexpr int BOX_BYTES = 64 * 64 * 2;
constexpr int OFF_CS = NBLK * BLK;
constexpr int OFF_BAR = OFF_CS + 5 * 512;
constexpr int SMEM_BYTES = OFF_BAR + 448;
constexpr int OFF_STAT = OFF_CS + 3 * 512;

constexpr int BAR_XFULL = 0, BAR_BFULL = 8, BAR_FULL = 14, BAR_CSRDY = 22, BAR_ABOK = 26, BAR_HOK = 27, BAR_EPOCH = 28,
              BAR_ABPOLL = 29, BAR_HPOLL = 30, BAR_XFREE = 31, BAR_PREP = 32,
              BAR_BEMPTY = 33, BAR_PUB = 39, BAR_ABST = 40,
              BAR_EMPTY = 41, BAR_DONE = 49, BAR_STATFREE = 50,
              BAR_HST = 51, NUM_BARS = 52;

constexpr int CNT_TICKET = 0, CNT_AB = 1, CNT_H = 2;
constexpr unsigned N_AB = 128, N_H = 8;

enum { M_X = 0, M_WR, M_WI, M_WG, M_WU, M_CR, M_CI, M_OUTI, M_WD, M_OUT, NUM_MAPS };

struct Params {
    const __nv_bfloat16 *x, *wr, *wi, *wg, *wu, *wd;
    uint32_t zero;
    CUtensorMap m[NUM_MAPS];
};

__device__ __align__(1024) uint8_t g_AB[64 * 4 * BLK];
__device__ __align__(1024) uint8_t g_H[16 * 28 * BLK];
__device__ __align__(128) uint2 g_cs[2 * F_];
__device__ __align__(128) uint2 g_rs[2 * D_];
__device__ __align__(128) uint4 g_st[S_];
__device__ __align__(128) unsigned g_cnt[(CNT_H + 16) * 32];

#define TLP(idx)
#define TL(role, idx)
#define TLC(idx)

__device__ __forceinline__ uint32_t smem_u32(const void* p) { return (uint32_t)__cvta_generic_to_shared(p); }
__device__ __forceinline__ int read_ctaid() {
    int r;
    asm volatile("mov.u32 %0, %%ctaid.x;" : "=r"(r));
    return r;
}
__device__ __forceinline__ int read_tid() {
    int r;
    asm volatile("mov.u32 %0, %%tid.x;" : "=r"(r));
    return r;
}
__device__ __forceinline__ bool elect_one() {
    uint32_t r;
    asm volatile("{\n.reg .pred p;\nelect.sync _|p, 0xffffffff;\nselp.u32 %0, 1, 0, p;\n}" : "=r"(r));
    return r;
}
__device__ __forceinline__ void mbar_init(uint32_t bar, uint32_t cnt) {
    asm volatile("mbarrier.init.shared::cta.b64 [%0], %1;" ::"r"(bar), "r"(cnt) : "memory");
}
__device__ __forceinline__ void mbar_expect_tx(uint32_t bar, uint32_t bytes) {
    asm volatile("mbarrier.arrive.expect_tx.shared::cta.b64 _, [%0], %1;" ::"r"(bar), "r"(bytes) : "memory");
}
__device__ __forceinline__ void mbar_arrive(uint32_t bar) {
    asm volatile("mbarrier.arrive.shared::cta.b64 _, [%0];" ::"r"(bar) : "memory");
}
__device__ __forceinline__ void mbar_arrive_n(uint32_t bar, uint32_t n) {
    asm volatile("mbarrier.arrive.shared::cta.b64 _, [%0], %1;" ::"r"(bar), "r"(n) : "memory");
}
__device__ __forceinline__ bool mbar_try_wait(uint32_t bar, uint32_t parity) {
    uint32_t ok;
    asm volatile("{\n.reg .pred p;\nmbarrier.try_wait.parity.shared::cta.b64 p, [%1], %2;\nselp.u32 %0, 1, 0, p;\n}"
                 : "=r"(ok) : "r"(bar), "r"(parity) : "memory");
    return ok;
}
__device__ __forceinline__ void mbar_wait(uint32_t bar, uint32_t parity) {
    if (__builtin_expect(!mbar_try_wait(bar, parity), 0)) {
        int it = 0;
        while (!mbar_try_wait(bar, parity)) {
            if (++it > (1 << 20)) __trap();
        }
    }
}
__device__ __forceinline__ void tma_load_2d(uint32_t dst, const CUtensorMap* m, uint32_t bar, int c0, int c1) {
    asm volatile("cp.async.bulk.tensor.2d.shared::cluster.global.mbarrier::complete_tx::bytes [%0], [%1, {%3, %4}], [%2];"
                 ::"r"(dst), "l"(m), "r"(bar), "r"(c0), "r"(c1) : "memory");
}
__device__ __forceinline__ void bulk_load_blk(uint32_t dst, const void* src, uint32_t bar) {
    asm volatile("cp.async.bulk.shared::cluster.global.mbarrier::complete_tx::bytes [%0], [%1], %2, [%3];"
                 ::"r"(dst), "l"(src), "n"(BLK), "r"(bar) : "memory");
}
__device__ __forceinline__ void tma_load_5d(uint32_t dst, const CUtensorMap* m, uint32_t bar, int c0, int c4) {
    asm volatile("cp.async.bulk.tensor.5d.shared::cluster.global.mbarrier::complete_tx::bytes [%0], [%1, {%3, %5, %5, %5, %4}], [%2];"
                 ::"r"(dst), "l"(m), "r"(bar), "r"(c0), "r"(c4), "r"(0) : "memory");
}
__device__ __forceinline__ void tma_store_2d(const CUtensorMap* m, uint32_t src, int c0, int c1) {
    asm volatile("cp.async.bulk.tensor.2d.global.shared::cta.bulk_group [%0, {%2, %3}], [%1];"
                 ::"l"(m), "r"(src), "r"(c0), "r"(c1) : "memory");
}
__device__ __forceinline__ void tma_red_add_2d(const CUtensorMap* m, uint32_t src, int c0, int c1) {
    asm volatile("cp.reduce.async.bulk.tensor.2d.global.shared::cta.add.tile.bulk_group [%0, {%2, %3}], [%1];"
                 ::"l"(m), "r"(src), "r"(c0), "r"(c1) : "memory");
}
__device__ __forceinline__ void tma_prefetch_2d(const CUtensorMap* m, int c0, int c1) {
    asm volatile("cp.async.bulk.prefetch.tensor.2d.L2.global [%0, {%1, %2}];" ::"l"(m), "r"(c0), "r"(c1) : "memory");
}
__device__ __forceinline__ void bulk_prefetch(const void* src, uint32_t bytes) {
    asm volatile("cp.async.bulk.prefetch.L2.global [%0], %1;" ::"l"(src), "r"(bytes) : "memory");
}
__device__ __forceinline__ void prefetch_map(const CUtensorMap* m) {
    asm volatile("prefetch.tensormap [%0];" ::"l"(m) : "memory");
}
__device__ __forceinline__ void bulk_commit() { asm volatile("cp.async.bulk.commit_group;" ::: "memory"); }
template <int N> __device__ __forceinline__ void bulk_wait() {
    asm volatile("cp.async.bulk.wait_group %0;" ::"n"(N) : "memory");
}
template <int N> __device__ __forceinline__ void bulk_wait_read() {
    asm volatile("cp.async.bulk.wait_group.read %0;" ::"n"(N) : "memory");
}
__device__ __forceinline__ void fence_async_smem() { asm volatile("fence.proxy.async.shared::cta;" ::: "memory"); }
__device__ __forceinline__ void fence_async_global() { asm volatile("fence.proxy.async.global;" ::: "memory"); }
__device__ __forceinline__ void wgmma_fence() { asm volatile("wgmma.fence.sync.aligned;" ::: "memory"); }
__device__ __forceinline__ void wgmma_commit() { asm volatile("wgmma.commit_group.sync.aligned;" ::: "memory"); }
template <int N> __device__ __forceinline__ void wgmma_wait() {
    asm volatile("wgmma.wait_group.sync.aligned %0;" ::"n"(N) : "memory");
}
__device__ __forceinline__ uint32_t make_desc(uint32_t addr, uint32_t lbo) { return (addr >> 4) | ((lbo >> 4) << 16); }
constexpr uint32_t HI_128 = (1u << 30) | (1024 >> 4);
constexpr uint32_t HI_AB = (2u << 30) | (2048 >> 4);
constexpr uint32_t HI_H = (2u << 30) | (512 >> 4);
__device__ __forceinline__ void red_release(unsigned* p) {
    asm volatile("red.release.gpu.global.add.u32 [%0], 1;" ::"l"(p) : "memory");
}
__device__ __forceinline__ void wait_counter(const unsigned* p, unsigned target) {
    int it = 0;
    while (true) {
        unsigned v;
        asm volatile("ld.acquire.gpu.global.u32 %0, [%1];" : "=r"(v) : "l"(p) : "memory");
        if ((int)(v - target) >= 0) break;
        if (++it > (1 << 17)) __trap();
        __nanosleep(40);
    }
}
__device__ __forceinline__ uint4 ldg_nc(const void* p) {
    uint4 v;
    asm volatile("ld.global.nc.L1::no_allocate.L2::256B.v4.u32 {%0,%1,%2,%3}, [%4];"
                 : "=r"(v.x), "=r"(v.y), "=r"(v.z), "=r"(v.w) : "l"(p));
    return v;
}
__device__ __forceinline__ uint4 lds128(uint32_t a) {
    uint4 v;
    asm volatile("ld.shared.v4.u32 {%0,%1,%2,%3}, [%4];" : "=r"(v.x), "=r"(v.y), "=r"(v.z), "=r"(v.w) : "r"(a) : "memory");
    return v;
}
__device__ __forceinline__ float4 ld_generic(uint64_t a) {
    float4 v;
    asm volatile("ld.v4.f32 {%0,%1,%2,%3}, [%4];" : "=f"(v.x), "=f"(v.y), "=f"(v.z), "=f"(v.w) : "l"(a) : "memory");
    return v;
}
__device__ __forceinline__ void stg128(void* dst, const uint32_t (&o)[4]) {
    asm volatile("st.global.v4.u32 [%0], {%1,%2,%3,%4};" ::"l"(dst), "r"(o[0]), "r"(o[1]), "r"(o[2]), "r"(o[3]) : "memory");
}
__device__ __forceinline__ float2 lds64f(uint32_t a) {
    float2 v;
    asm volatile("ld.shared.v2.f32 {%0,%1}, [%2];" : "=f"(v.x), "=f"(v.y) : "r"(a) : "memory");
    return v;
}
__device__ __forceinline__ void stmatrix_x4(uint32_t a, uint32_t r0, uint32_t r1, uint32_t r2, uint32_t r3) {
    asm volatile("stmatrix.sync.aligned.m8n8.x4.shared.b16 [%0], {%1,%2,%3,%4};"
                 ::"r"(a), "r"(r0), "r"(r1), "r"(r2), "r"(r3) : "memory");
}
__device__ __forceinline__ uint32_t pack_bf16(float lo, float hi) {
    uint32_t r;
    asm("cvt.rn.bf16x2.f32 %0, %1, %2;" : "=r"(r) : "f"(hi), "f"(lo));
    return r;
}
__device__ __forceinline__ uint32_t pack_out(float lo, float hi) {
    uint32_t r = pack_bf16(lo, hi);
    if (SCALE_EXP) asm("mul.rn.bf16x2 %0, %0, %1;" : "+r"(r) : "r"(SCALE_UP2));
    return r;
}
__device__ __forceinline__ float tanh_fast(float x) {
    float y;
    asm("tanh.approx.f32 %0, %1;" : "=f"(y) : "f"(x));
    return y;
}
__device__ __forceinline__ float after(float v, float dep, uint32_t zero) {
    uint32_t r;
    asm("lop3.b32 %0, %1, %2, %3, 0xF8;" : "=r"(r) : "r"(__float_as_uint(v)), "r"(__float_as_uint(dep)), "r"(zero));
    return __uint_as_float(r);
}
__device__ __forceinline__ void turn_wait(int wg) { asm volatile("bar.sync %0, 256;" ::"r"(1 + wg) : "memory"); }
__device__ __forceinline__ void turn_give(int wg) { asm volatile("bar.arrive %0, 256;" ::"r"(1 + wg) : "memory"); }

#define OPS8(c, d, b) c(d[b]), c(d[b + 1]), c(d[b + 2]), c(d[b + 3]), c(d[b + 4]), c(d[b + 5]), c(d[b + 6]), c(d[b + 7])
#define OPS32(c, d, b) OPS8(c, d, b), OPS8(c, d, b + 8), OPS8(c, d, b + 16), OPS8(c, d, b + 24)
#define REGS64 \
    "{%0,%1,%2,%3,%4,%5,%6,%7,%8,%9,%10,%11,%12,%13,%14,%15,%16,%17,%18,%19,%20,%21,%22,%23,%24,%25,%26,%27,%28,%29,%30,%31," \
    "%32,%33,%34,%35,%36,%37,%38,%39,%40,%41,%42,%43,%44,%45,%46,%47,%48,%49,%50,%51,%52,%53,%54,%55,%56,%57,%58,%59,%60,%61,%62,%63}"

#define DESC_PRE "{\n.reg .b64 da, db;\nmov.b64 da, {%64, %67};\nmov.b64 db, {%65, %68};\n"
template <int TB, int ACC, uint32_t HA, uint32_t HB>
__device__ __forceinline__ void wgmma_n128(float (&d)[64], uint32_t da, uint32_t db) {
    if (ACC)
        asm volatile(DESC_PRE "wgmma.mma_async.sync.aligned.m64n128k16.f32.bf16.bf16 " REGS64 ", da, db, 1, 1, 1, 0, %66;\n}"
                     : OPS32("+f", d, 0), OPS32("+f", d, 32) : "r"(da), "r"(db), "n"(TB), "n"(HA), "n"(HB));
    else
        asm volatile(DESC_PRE "wgmma.mma_async.sync.aligned.m64n128k16.f32.bf16.bf16 " REGS64 ", da, db, 0, 1, 1, 0, %66;\n}"
                     : OPS32("=f", d, 0), OPS32("=f", d, 32) : "r"(da), "r"(db), "n"(TB), "n"(HA), "n"(HB));
}

template <int ACC>
__device__ __forceinline__ void wgmma_n8_ta(float (&d)[4], uint32_t da, uint64_t db) {
    if (ACC)
        asm volatile("{\n.reg .b64 da;\nmov.b64 da, {%4, 0x40000040};\n"
                     "wgmma.mma_async.sync.aligned.m64n8k16.f32.bf16.bf16 {%0,%1,%2,%3}, da, %5, 1, 1, 1, 1, 0;\n}"
                     : "+f"(d[0]), "+f"(d[1]), "+f"(d[2]), "+f"(d[3]) : "r"(da), "l"(db));
    else
        asm volatile("{\n.reg .b64 da;\nmov.b64 da, {%4, 0x40000040};\n"
                     "wgmma.mma_async.sync.aligned.m64n8k16.f32.bf16.bf16 {%0,%1,%2,%3}, da, %5, 0, 1, 1, 1, 0;\n}"
                     : "=f"(d[0]), "=f"(d[1]), "=f"(d[2]), "=f"(d[3]) : "r"(da), "l"(db));
}

struct OpAb { static constexpr int TB = 0, AM = 512, AH = 4, BK = 2, LBO = 16; static constexpr uint32_t HA = HI_128, HB = HI_128; };
struct OpGu { static constexpr int TB = 1, AM = 512, AH = 4, BK = 128, LBO = 8192; static constexpr uint32_t HA = HI_128, HB = HI_128; };
struct OpDft { static constexpr int TB = 1, AM = 512, AH = 4, BK = 256, LBO = 512; static constexpr uint32_t HA = HI_128, HB = HI_AB; };
struct OpDown { static constexpr int TB = 1, AM = 256, AH = 512, BK = 128, LBO = 8192; static constexpr uint32_t HA = HI_H, HB = HI_128; };

template <class Op, int ACC, int H>
__device__ __forceinline__ void mma_half(float (&e)[2][64], uint32_t da, uint32_t db) {
    da += H * Op::AH;
    db += H * 2 * Op::BK;
    wgmma_fence();
    wgmma_n128<Op::TB, ACC, Op::HA, Op::HB>(e[0], da, db);
    wgmma_n128<Op::TB, ACC, Op::HA, Op::HB>(e[1], da + Op::AM, db);
    wgmma_n128<Op::TB, 1, Op::HA, Op::HB>(e[0], da + 2, db + Op::BK);
    wgmma_n128<Op::TB, 1, Op::HA, Op::HB>(e[1], da + Op::AM + 2, db + Op::BK);
    wgmma_commit();
}

__device__ __forceinline__ constexpr int x_blk(int kb) { return kb < 3 ? kb : 2 * kb - 2; }
__device__ __forceinline__ constexpr int w_blk(int sl) { return 3 + 2 * sl; }

__device__ __forceinline__ constexpr int ring_start(int s) { return s < NSOLO ? 2 * s : 3 * s - NSOLO; }
__device__ __forceinline__ constexpr int ring_need(int c) {
    return c < NBLK ? c / 2 - 7 : (c - NBLK < 2 * NSOLO ? (c - NBLK) / 2 : NSOLO + (c - NBLK - 2 * NSOLO) / 3);
}

__device__ __forceinline__ void store_tagged(uint2* dst, float v, uint32_t tag) {
    asm volatile("st.relaxed.gpu.global.v2.u32 [%0], {%1, %2};" ::"l"(dst), "r"(__float_as_uint(v)), "r"(tag) : "memory");
}
__device__ __forceinline__ void store_tagged2(uint4* dst, float v0, float v1, uint32_t tag) {
    asm volatile("st.relaxed.gpu.global.v4.u32 [%0], {%1, %3, %2, %3};"
                 ::"l"(dst), "r"(__float_as_uint(v0)), "r"(__float_as_uint(v1)), "r"(tag) : "memory");
}
__device__ __forceinline__ uint4 ld_relaxed(const void* src) {
    uint4 v;
    asm volatile("ld.relaxed.gpu.global.v4.u32 {%0,%1,%2,%3}, [%4];"
                 : "=r"(v.x), "=r"(v.y), "=r"(v.z), "=r"(v.w) : "l"(src) : "memory");
    return v;
}
__device__ __forceinline__ float bf_lo(uint32_t u) { return __uint_as_float(u << 16); }
__device__ __forceinline__ float bf_hi(uint32_t u) { return __uint_as_float(u & 0xffff0000u); }
__device__ __forceinline__ uint32_t word(const uint4& v, int j) { return j == 0 ? v.x : (j == 1 ? v.y : (j == 2 ? v.z : v.w)); }

__device__ __forceinline__ void aux_column_sums(const Params& p, uint32_t base, int a, int warp, int lane) {
    constexpr int SLOT = 8 * BOX_BYTES;
    const uint32_t full = base + OFF_BAR, empty = full + 24, tag_addr = full + 48;
    const uint32_t t0 = clock();
    if (warp == 8) {
        if (elect_one()) {
#pragma unroll
            for (int i = 0; i < 3; i++) { mbar_init(full + 8 * i, 1); mbar_init(empty + 8 * i, 4); }
            asm volatile("fence.mbarrier_init.release.cluster;" ::: "memory");
            const uint32_t tag = atomicAdd(&g_cnt[CNT_TICKET], 1u) / NCTA + 1;
            asm volatile("st.shared.u32 [%0], %1;" ::"r"(tag_addr), "r"(tag) : "memory");
        }
    } else if (warp == 0 && lane < 16) {
        asm volatile("st.shared.v4.u32 [%0], {%1,%1,%1,%1};" ::"r"(base + OFF_CS + lane * 16), "r"(0x3F803F80u) : "memory");
        fence_async_smem();
    }
    __syncthreads();
    if (warp == 8) {
        if (elect_one()) {
            while ((uint32_t)clock() - t0 < AUX_DELAY) {}
            const CUtensorMap* m = &p.m[(a & 1) ? M_WU : M_WG];
#pragma unroll 1
            for (int j = 0; j < 14; j++) {
                const int sl = j % 3;
                if (j >= 3) mbar_wait(empty + 8 * sl, (j / 3 - 1) & 1);
                mbar_expect_tx(full + 8 * sl, SLOT);
#pragma unroll
                for (int kb = 0; kb < 8; kb++)
                    tma_load_2d(base + sl * SLOT + kb * BOX_BYTES, m, full + 8 * sl, (2 * j + (a >> 1)) * 64, kb * 64);
            }
        }
    } else if (warp < 4 * AUX_WGS) {
        uint32_t tag;
        asm volatile("ld.shared.u32 %0, [%1];" : "=r"(tag) : "r"(tag_addr) : "memory");
        const uint64_t ones = (uint64_t)make_desc(base + OFF_CS, 128) | ((uint64_t)(256 >> 4) << 32);
#pragma unroll 1
        for (int j = warp >> 2; j < 14; j += AUX_WGS) {
            const int sl = j % 3;
            const uint32_t da = make_desc(base + sl * SLOT, 8192);
            float d[4][4];
            if (j >= 3) mbar_wait(empty + 8 * sl, (j / 3 - 1) & 1);
            mbar_wait(full + 8 * sl, (j / 3) & 1);
            wgmma_fence();
#pragma unroll
            for (int k = 0; k < 4; k++) wgmma_n8_ta<0>(d[k], da + k * 128, ones);
#pragma unroll
            for (int k = 4; k < 32; k++) wgmma_n8_ta<1>(d[k & 3], da + k * 128, ones);
            wgmma_commit();
            wgmma_wait<0>();
            if (lane == 0) mbar_arrive(empty + 8 * sl);
            if ((lane & 3) == 0) {
                uint2* dst = g_cs + (a & 1) * F_ + (2 * j + (a >> 1)) * 64 + (warp & 3) * 16 + (lane >> 2);
                store_tagged(dst, (d[0][0] + d[1][0]) + (d[2][0] + d[3][0]), tag);
                store_tagged(dst + 8, (d[0][2] + d[1][2]) + (d[2][2] + d[3][2]), tag);
            }
            if ((threadIdx.x & 127) == 0) TL(2, j);
        }
    }
}

#define CTA_COORDS                                                                                          \
    const int b = read_ctaid() - NAUX, tid = read_tid();                                                    \
    [[maybe_unused]] const int warp = __shfl_sync(0xffffffffu, tid >> 5, 0), lane = tid & 31;               \
    [[maybe_unused]] const int wg = warp >> 2, wq = warp & 3;                                               \
    [[maybe_unused]] const int nh = b & 1, rb = (b >> 1) & 15, ks = b >> 5, role = nh * 4 + ks;             \
    [[maybe_unused]] const int nunits = ks >= 2 ? 5 : 4, lead_wg = nunits & 1, boff = ks >= 2 ? 2 : 4;      \
    [[maybe_unused]] const int ndft = ks >= 2 ? 14 : 18, nk = ndft + 7, dft0 = ks >= 2 ? 8 + ks * 14 : ks * 18; \
    [[maybe_unused]] auto gu_chunk = [=](int u) { return u < 4 ? (u - 1) * 8 + role : 22 + nh * 2 + ks; }

template <int V> struct IntC { static constexpr int value = V; };

__global__ void __launch_bounds__(384, 1) fused_kernel(const __grid_constant__ Params p) {
    extern __shared__ __align__(1024) uint8_t smem_raw[];
    const uint32_t base = smem_u32(smem_raw);
    const uint32_t bars = base + OFF_BAR;
    auto bar = [&](int i) { return bars + 8 * i; };
    const uint32_t epoch_addr = bars + 8 * NUM_BARS;

    const int warp0 = __shfl_sync(0xffffffffu, threadIdx.x >> 5, 0);
    if (blockIdx.x < NAUX) {
        aux_column_sums(p, base, blockIdx.x, warp0, threadIdx.x & 31);
        return;
    }

    if (threadIdx.x == 256) TL(2, 10);
    if (warp0 >= 1 && warp0 <= EARLY_PF) {
        CTA_COORDS;
        const __nv_bfloat16* src = lane < 16 ? p.x + (size_t)(rb * 128 + role * 16 + lane) * D_
                                             : (nh ? p.wi : p.wr) + (size_t)(ks * 128 + rb * 8 + (lane & 7)) * D_;
        const uint32_t t0 = clock();
        while ((uint32_t)clock() - t0 < (warp - 1) * EARLY_GAP) {}
        if (lane < 24) asm volatile("prefetch.global.L2 [%0];" ::"l"(src + (warp - 1) * 64) : "memory");
    }
    if (warp0 == 8) {
        CTA_COORDS;
        const CUtensorMap* mab = &p.m[nh ? M_WI : M_WR];
        const bool lead = elect_one();
        auto first_loads = [&](int kb) {
            mbar_expect_tx(bar(BAR_XFULL + kb), BLK);
            tma_load_2d(base + x_blk(kb) * BLK, &p.m[M_X], bar(BAR_XFULL + kb), kb * 64, rb * 128);
            if (kb < BSLOTS) {
                const int sl = kb + boff >= BSLOTS ? kb + boff - BSLOTS : kb + boff;
                mbar_expect_tx(bar(BAR_BFULL + sl), BLK);
                tma_load_5d(base + w_blk(sl) * BLK, mab, bar(BAR_BFULL + sl), kb * 64, ks * 4);
            }
        };
        if (lead) {
            mbar_init(bar(BAR_XFULL), 1);
            mbar_init(bar(BAR_BFULL + boff), 1);
            asm volatile("fence.mbarrier_init.release.cluster;" ::: "memory");
            first_loads(0);
            TL(2, 0);
#pragma unroll
            for (int i = 1; i < BAR_FULL; i++)
                if (i != BAR_BFULL + boff) mbar_init(bar(i), 1);
#pragma unroll
            for (int i = 0; i < 4; i++)
                if (i < boff) mbar_arrive(bar(BAR_BFULL + i));
            asm volatile("fence.mbarrier_init.release.cluster;" ::: "memory");
        }
        asm volatile("bar.arrive 4, 384;" ::: "memory");
        if (lead) {
#pragma unroll
            for (int kb = FAST_FIRST; kb < 8; kb++) first_loads(kb);
            TL(2, 6);
        }
        asm volatile("bar.sync 5, 64;" ::: "memory");
    } else {
        if (warp0 == 0) {
            CTA_COORDS;
            if (elect_one()) {
                if (base & 1023) __trap();
#pragma unroll
                for (int i = BAR_FULL; i < BAR_HST; i++) mbar_init(bar(i), i < BAR_BEMPTY ? 1 : (i < BAR_EMPTY ? 4 : 8));
                mbar_init(bar(BAR_HST), 4 * (nunits - 1));
#pragma unroll
                for (int i = 0; i < 4; i++)
                    if (i < boff) mbar_arrive_n(bar(BAR_BEMPTY + i), 4);
                asm volatile("fence.mbarrier_init.release.cluster;" ::: "memory");
            }
            asm volatile("bar.arrive 5, 64;" ::: "memory");
        }
        asm volatile("bar.sync 4, 384;" ::: "memory");
    }

    if (warp0 >= 8) {
        if (warp0 == 8) {
            CTA_COORDS;
            if (elect_one()) {
                const CUtensorMap* mab = &p.m[nh ? M_WI : M_WR];
                int ls = boff;
                uint32_t ph = 0;
                uint32_t fb, sb;
                auto next_slot = [&]() {
                    mbar_wait(bar(BAR_BEMPTY + ls), ph);
                    fb = bar(BAR_BFULL + ls);
                    sb = base + w_blk(ls) * BLK;
                    mbar_expect_tx(fb, BLK);
                    if (++ls == BSLOTS) { ls = 0; ph ^= 1; }
                };
#pragma unroll
                for (int kb = BSLOTS; kb < 8; kb++) {
                    next_slot();
                    tma_load_5d(sb, mab, fb, kb * 64, ks * 4);
                }
#pragma unroll 1
                for (int u = 1; u < nunits; u++) {
                    const int c = gu_chunk(u) * 64;
#pragma unroll 1
                    for (int k = 0; k < D_; k += 64) {
                        next_slot();
                        tma_load_2d(sb, &p.m[M_WG], fb, c, k);
                        tma_load_2d(sb + BOX_BYTES, &p.m[M_WU], fb, c, k);
                    }
                }
                TL(2, 1);
                mbar_wait(bar(BAR_XFREE), 0);
                mbar_wait(bar(BAR_ABOK), 0);
                fence_async_global();
                TL(2, 2);
                const CUtensorMap* mc = &p.m[dft0 < 32 ? M_CR : M_CI];
                const int cl = nh * 2 + lead_wg, cf = nh * 2 + (lead_wg ^ 1), arow = rb * 128;
                const uint8_t* abl = g_AB + (size_t)(dft0 * 4 + cl) * BLK;
                const uint8_t* abf = g_AB + (size_t)(dft0 * 4 + cf) * BLK;
                auto wait_step = [&](int t) { mbar_wait(bar(BAR_EMPTY + (t & 7)), (t >> 3) & 1); };
                auto blk = [&](int i) { return base + (i >= NBLK ? i - NBLK : i) * BLK; };
                auto wait_block = [&](int c) {
                    if (c < 2 || ring_need(c) == ring_need(c - 1)) return;
                    if (ring_need(c) < 0) mbar_wait(bar(BAR_BEMPTY + BSLOTS + ring_need(c)), ph);
                    else wait_step(ring_need(c));
                };
                constexpr int NFIRST = NSOLO + 5;
                static_assert(NBLK == 14 && NFIRST <= 14, "steady state from step NFIRST on, one map before it");
#pragma unroll
                for (int s = 0; s < NFIRST; s++) {
                    const int c = ring_start(s);
                    fb = bar(BAR_FULL + (s & 7));
                    wait_block(c);
                    mbar_expect_tx(fb, s < NSOLO ? 2 * BLK : 3 * BLK);
                    tma_load_2d(base + c % NBLK * BLK, mc, fb, ((dft0 + s) * 64) & (S_ - 1), arow);
                    wait_block(c + 1);
                    bulk_load_blk(base + (c + 1) % NBLK * BLK, (s < NSOLO ? abl : abf) + s * 4 * BLK, fb);
                    if (s >= NSOLO) {
                        wait_block(c + 2);
                        bulk_load_blk(base + (c + 2) % NBLK * BLK, abl + s * 4 * BLK, fb);
                    }
                    if (s == NFIRST - 2) mbar_arrive(bar(BAR_HPOLL));
                }
                int pos = ring_start(NFIRST) % NBLK;
#pragma unroll 1
                for (int s = NFIRST; s < ndft; s++) {
                    const int k = (dft0 + s) * 64;
                    fb = bar(BAR_FULL + (s & 7));
                    mbar_expect_tx(fb, 3 * BLK);
                    tma_load_2d(blk(pos), &p.m[k < S_ ? M_CR : M_CI], fb, k & (S_ - 1), arow);
                    bulk_load_blk(blk(pos + 1), abf + s * 4 * BLK, fb);
                    wait_step(s - 4);
                    bulk_load_blk(blk(pos + 2), abl + s * 4 * BLK, fb);
                    pos += 3;
                    if (pos >= NBLK) pos -= NBLK;
                }
                TL(2, 3);
                mbar_wait(bar(BAR_HOK), 0);
                fence_async_global();
                TL(2, 4);
#pragma unroll 1
                for (int s = ndft; s < nk; s++) {
                    const int kb = ks * 7 + s - ndft;
                    fb = bar(BAR_FULL + (s & 7));
                    mbar_expect_tx(fb, 3 * BLK);
                    bulk_load_blk(blk(pos), g_H + (size_t)(rb * 28 + kb) * BLK, fb);
                    tma_load_5d(blk(pos + 1), &p.m[M_WD], fb, cf * 128, kb * 2);
                    tma_load_5d(blk(pos + 1) + BOX_BYTES, &p.m[M_WD], fb, cf * 128 + 64, kb * 2);
                    wait_step(s - 4);
                    tma_load_5d(blk(pos + 2), &p.m[M_WD], fb, cl * 128, kb * 2);
                    tma_load_5d(blk(pos + 2) + BOX_BYTES, &p.m[M_WD], fb, cl * 128 + 64, kb * 2);
                    pos += 3;
                    if (pos >= NBLK) pos -= NBLK;
                }
#pragma unroll
                for (int j = 0; j < NSOLO; j++) {
                    fb = bar(BAR_FULL + ((nk + j) & 7));
                    if (j == 1) wait_step(nk - 4);
                    if (j == 4) wait_step(nk - 2);
                    if (j >= 6) wait_step(nk + j - 6);
                    mbar_expect_tx(fb, 2 * BLK);
                    tma_load_2d(blk(pos), mc, fb, ((dft0 + j) * 64) & (S_ - 1), arow);
                    if (j == 2) wait_step(nk - 3);
                    if (j == 5) wait_step(nk - 1);
                    bulk_load_blk(blk(pos + 1), abf + j * 4 * BLK, fb);
                    pos += j == 5 ? 4 : 2;
                    if (pos >= NBLK) pos -= NBLK;
                }
                TL(2, 5);
            }
        } else {
            CTA_COORDS;
            const int w = warp - 9;
            uint32_t tag;
            if (w == 1 && lane == 0) {
                tag = atomicAdd(&g_cnt[CNT_TICKET], 1u) / NCTA + 1;
                asm volatile("st.shared.u32 [%0], %1;" ::"r"(epoch_addr), "r"(tag) : "memory");
                mbar_arrive(bar(BAR_EPOCH));
            }
            float wsum = 0.f;
            const int wrow = role * 128 + rb * 8 + w * 2 + (lane >> 3);
            if (w != 1) {
                const __nv_bfloat16* ws = (nh ? p.wi : p.wr) + (size_t)(wrow & 511) * D_ + (lane & 7) * 8;
                uint4 wv[8];
#pragma unroll
                for (int i = 0; i < 8; i++) wv[i] = ldg_nc(ws + i * 64);
#pragma unroll
                for (int i = 0; i < 32; i++) wsum = (wsum + bf_lo(word(wv[i >> 2], i & 3))) + bf_hi(word(wv[i >> 2], i & 3));
#pragma unroll
                for (int o = 1; o < 8; o <<= 1) wsum += __shfl_xor_sync(0xffffffffu, wsum, o);
            } else if (elect_one()) {
                mbar_wait(bar(BAR_XFULL), 0);
                prefetch_map(&p.m[M_WG]);
                prefetch_map(&p.m[M_WU]);
                mbar_wait(bar(BAR_XFULL + PFW_AT), 0);
                bulk_prefetch((b < 64 ? p.wg : p.wu) + (size_t)(b & 63) * 8 * F_, 8 * F_ * 2);
            }
            __syncwarp();
            mbar_wait(bar(BAR_EPOCH), 0);
            asm volatile("ld.shared.u32 %0, [%1];" : "=r"(tag) : "r"(epoch_addr) : "memory");
            if (w != 1 && (lane & 7) == 0) store_tagged(g_rs + wrow, wsum, tag);
            if (w == 0 && lane == 0) TL(2, 7);
            __syncwarp();
            if (w == 0) {
                if (elect_one()) {
                    auto prefetch_dft = [&](int i0, int i1) {
#pragma unroll 1
                        for (int i = i0 + nh; i < i1; i += 2) {
                            const int kb = dft0 + i;
                            tma_prefetch_2d(&p.m[kb < 32 ? M_CR : M_CI], (kb & 31) * 64, rb * 128);
                            __nanosleep(PF_GAP);
                        }
                    };
                    mbar_wait(bar(BAR_PREP), 0);
#pragma unroll 1
                    for (int i = M_CR; i < NUM_MAPS; i++) prefetch_map(&p.m[i]);
                    prefetch_dft(0, PF_A);
                    mbar_wait(bar(BAR_ABPOLL), 0);
                    wait_counter(&g_cnt[CNT_AB], tag * N_AB);
                    mbar_arrive(bar(BAR_ABOK));
                    TL(2, 26);
                    prefetch_dft(PF_A, PF_B < ndft ? PF_B : ndft);
                    bulk_prefetch(p.wd + (size_t)b * 14 * D_, 14 * D_ * 2);
                    mbar_wait(bar(BAR_HPOLL), 0);
                    wait_counter(&g_cnt[(CNT_H + rb) * 32], tag * N_H);
                    mbar_arrive(bar(BAR_HOK));
                    TL(2, 27);
                    mbar_wait(bar(BAR_DONE), 0);
                }
            } else if (w == 1) {
                mbar_wait(bar(BAR_PUB), 0);
                __nanosleep(POLL_DELAY);
                uint4 v[6];
                int it = 0;
                while (true) {
#pragma unroll
                    for (int i = 0; i < 4; i++) v[i] = ld_relaxed(g_st + rb * 128 + i * 32 + lane);
#pragma unroll
                    for (int i = 0; i < 2; i++) v[4 + i] = ld_relaxed(g_rs + role * 128 + lane * 4 + i * 2);
                    bool ok = true;
#pragma unroll
                    for (int i = 0; i < 6; i++) ok = ok && v[i].y == tag && v[i].w == tag;
                    if (__all_sync(0xffffffffu, ok)) break;
                    if (++it > (1 << 16)) __trap();
                }
#pragma unroll
                for (int i = 0; i < 4; i++)
                    asm volatile("st.shared.v2.u32 [%0], {%1,%2};" ::"r"(base + OFF_STAT + (i * 32 + lane) * 8), "r"(v[i].x), "r"(v[i].z) : "memory");
                asm volatile("st.shared.v4.u32 [%0], {%1,%2,%3,%4};"
                             ::"r"(base + OFF_CS + lane * 16), "r"(v[4].x), "r"(v[4].z), "r"(v[5].x), "r"(v[5].z) : "memory");
                __syncwarp();
                if (elect_one()) {
                    mbar_arrive(bar(BAR_PREP));
                    TL(2, 8);
                    mbar_wait(bar(BAR_ABST), 0);
                    TL(2, 24);
                    red_release(&g_cnt[CNT_AB]);
                    mbar_arrive(bar(BAR_ABPOLL));
                    TL(2, 12);
                    const uint32_t xsrc = base + (role < 3 ? role : 2 * role - 2) * BLK;
                    tma_store_2d(&p.m[M_OUTI], xsrc, role * 64, rb * 128);
                    __nanosleep(500);
                    tma_store_2d(&p.m[M_OUTI], xsrc + BOX_BYTES, role * 64, rb * 128 + 64);
                    bulk_commit();
                    bulk_wait<0>();
                    mbar_arrive(bar(BAR_XFREE));
                    mbar_wait(bar(BAR_HST), 0);
                    red_release(&g_cnt[(CNT_H + rb) * 32]);
                    TL(2, 29);
                }
            } else {
                mbar_wait(bar(BAR_PREP), 0);
#pragma unroll 1
                for (int u = 1; u < nunits; u++) {
                    if (u == 3) mbar_wait(bar(BAR_STATFREE), 0);
                    const uint2* s0 = g_cs + gu_chunk(u) * 64 + lane * 2;
                    uint4 vg, vu;
                    int it = 0;
                    while (true) {
                        vg = ld_relaxed(s0);
                        vu = ld_relaxed(s0 + F_);
                        if (__all_sync(0xffffffffu, vg.y == tag && vg.w == tag && vu.y == tag && vu.w == tag)) break;
                        if (++it > (1 << 16)) __trap();
                        __nanosleep(CS_SLEEP);
                    }
                    asm volatile("st.shared.v4.u32 [%0], {%1,%2,%3,%4};"
                                 ::"r"(base + OFF_CS + u * 512 + lane * 16), "r"(vg.x), "r"(vg.z), "r"(vu.x), "r"(vu.z) : "memory");
                    __syncwarp();
                    if (lane == 0) { mbar_arrive(bar(BAR_CSRDY + u - 1)); TL(2, 18 + u); }
                }
            }
        }
    } else {
        {
        CTA_COORDS;
        const int q = lane & 3;
        float nm[4], rs[4];
        auto load_stats = [&]() {
            mbar_wait(bar(BAR_PREP), 0);
#pragma unroll
            for (int i = 0; i < 4; i++) {
                const float2 v = lds64f(base + OFF_STAT + ((i >> 1) * 64 + wq * 16 + (i & 1) * 8 + (lane >> 2)) * 8);
                nm[i] = v.x;
                rs[i] = v.y;
            }
            __syncwarp();
            if (lane == 0) mbar_arrive(bar(BAR_STATFREE));
        };
        if (wg == 1) {
            turn_give(0);
            const int row0 = rb * 128 + role * 16 + wq * 4;
            const uint32_t xs = base + (role * 16 + wq * 4) * 128 + lane * 16;
            float s1 = 0.f, s2 = 0.f;
#pragma unroll
            for (int kb = 0; kb < 8; kb++) {
                mbar_wait(bar(BAR_XFULL + kb), 0);
                const uint4 xv = lds128(xs + x_blk(kb) * BLK);
#pragma unroll
                for (int i = 0; i < 4; i++) {
                    const float lo = bf_lo(word(xv, i)), hi = bf_hi(word(xv, i));
                    s1 = (s1 + lo) + hi;
                    s2 = fmaf(hi, hi, fmaf(lo, lo, s2));
                }
            }
            TLC(57);
#pragma unroll
            for (int o = 1; o < 8; o <<= 1) {
                s1 += __shfl_xor_sync(0xffffffffu, s1, o);
                s2 += __shfl_xor_sync(0xffffffffu, s2, o);
            }
            uint32_t tag;
            mbar_wait(bar(BAR_EPOCH), 0);
            asm volatile("ld.shared.u32 %0, [%1];" : "=r"(tag) : "r"(epoch_addr) : "memory");
            const float mean = s1 * (1.f / D_);
            const float rsv = rsqrtf(fmaxf(fmaf(-mean, mean, s2 * (1.f / D_)), 0.f) + 1e-5f);
            if ((lane & 7) == 0) store_tagged2(g_st + row0 + (lane >> 3), -mean, rsv, tag);
            __syncwarp();
            if (lane == 0) mbar_arrive(bar(BAR_PUB));
            TLC(58);
        }

        auto run_unit = [&](auto op, float (&e)[2][64], int u) {
            using Op = decltype(op);
            const uint32_t da = make_desc(base, 16);
            const uint32_t db0 = make_desc(base + w_blk(0) * BLK, Op::LBO);
            int sl = (u * 8 + boff) % BSLOTS, prev = 0;
            uint32_t ph = ((u * 8 + boff) / BSLOTS) & 1;
            turn_wait(wg);
#pragma unroll
            for (int kb = 0; kb < 8; kb++) {
                const uint32_t db = db0 + sl * (2 * BLK >> 4);
                if (Op::TB == 0) mbar_wait(bar(BAR_XFULL + kb), 0);
                mbar_wait(bar(BAR_BFULL + sl), ph);
                if (kb == 0) {
                    TLC((u >> 1) * 2);
                    mma_half<Op, 0, 0>(e, da, db);
                } else {
                    mma_half<Op, 1, 0>(e, da + x_blk(kb) * (BLK >> 4), db);
                    wgmma_wait<1>();
                    if (lane == 0) mbar_arrive(bar(BAR_BEMPTY + prev));
                }
                mma_half<Op, 1, 1>(e, da + x_blk(kb) * (BLK >> 4), db);
                prev = sl;
                if (++sl == BSLOTS) { sl = 0; ph ^= 1; }
            }
            turn_give(wg ^ 1);
            wgmma_wait<0>();
            if (lane == 0) mbar_arrive(bar(BAR_BEMPTY + prev));
            TLC(40 + (u >> 1) * 3);
        };

        const int atom_off = (lane >> 2) * 64 + ((q ^ (lane >> 3)) << 4);
        const uint64_t gen_cs = reinterpret_cast<uint64_t>(smem_raw) + OFF_CS + p.zero;
        if (wg == 0) {
            float e[2][64];
            run_unit(OpAb(), e, 0);
            load_stats();
            TLC(41);
            const uint64_t csb = gen_cs + q * 32;
            uint8_t* dst = g_AB + (size_t)((nh * 32 + rb * 2) * 4 + ks) * BLK + wq * 4096 + atom_off;
            const float sg = nh ? -SCALE_DOWN : SCALE_DOWN;
            float dep = 0.f;
            float4 n0 = ld_generic(csb), n1 = ld_generic(csb + 16);
#pragma unroll
            for (int j = 0; j < 4; j++) {
                const float c[8] = {n0.x, n0.y, n0.z, n0.w, n1.x, n1.y, n1.z, n1.w};
#pragma unroll
                for (int mr = 0; mr < 4; mr++) {
                    const float r = rs[mr] * sg;
                    uint32_t o[4];
#pragma unroll
                    for (int i = 0; i < 4; i++) {
                        const float* v = e[mr >> 1] + 16 * j + 4 * i + 2 * (mr & 1);
                        const float n = after(nm[mr], dep, p.zero);
                        const float v0 = fmaf(n, c[2 * i], v[0]) * r, v1 = fmaf(n, c[2 * i + 1], v[1]) * r;
                        o[i] = pack_bf16(v0, v1);
                        dep = AB_DEP == 0 ? v1 : __uint_as_float(o[i]);
                    }
                    stg128(dst + (mr >> 1) * 4 * BLK + (mr & 1) * 2048 + j * 512, o);
                    if (mr == 1 && j < 3) { n0 = ld_generic(csb + j * 128 + 128); n1 = ld_generic(csb + j * 128 + 144); }
                }
            }
            __syncwarp();
            if (lane == 0) mbar_arrive(bar(BAR_ABST));
            TLC(42);
        }
#pragma unroll 1
        for (int u = 2 - wg; u < nunits; u += 2) {
            float e[2][64];
            run_unit(OpGu(), e, u);
            if (u == 1) load_stats();
            mbar_wait(bar(BAR_CSRDY + u - 1), 0);
            TLC(41 + (u >> 1) * 3);
            const uint64_t csb = gen_cs + u * 512 + q * 16;
            uint8_t* dst = g_H + (size_t)(rb * 28 + gu_chunk(u)) * BLK + wq * 1024 + atom_off;
            const float k0 = 0.7978845608028654f, k1 = 0.7978845608028654f * 0.044715f;
            float dep = 0.f;
            float4 cn[2] = {ld_generic(csb), ld_generic(csb + 64)};
#pragma unroll
            for (int mj = 0; mj < 4; mj++) {
                const int m = mj >> 1, j = mj & 1;
                uint32_t o[2][4];
#pragma unroll
                for (int i = 0; i < 4; i++) {
                    const float4 c = cn[i & 1];
                    if (mj * 4 + i < 14) cn[i & 1] = ld_generic(csb + ((4 * j + i + 2) & 7) * 64);
#pragma unroll
                    for (int rr = 0; rr < 2; rr++) {
                        const float r = rs[2 * m + rr];
                        const float c0 = k0 * r, c1 = k1 * r * r * r, ch = (0.5f * SCALE_DOWN) * r * r;
                        float hv[2];
#pragma unroll
                        for (int t = 0; t < 2; t++) {
                            const float* v = e[m] + 16 * j + 4 * i + 2 * rr + t;
                            const float n = after(nm[2 * m + rr], dep, p.zero);
                            const float tg = fmaf(n, t ? c.y : c.x, v[0]);
                            const float tu = fmaf(n, t ? c.w : c.z, v[32]);
                            const float sq = tg * tg, pl = fmaf(sq, c1, c0), z = tg * pl;
                            const float wv = (tg * ch) * tu;
                            hv[t] = fmaf(wv, tanh_fast(z), wv);
                            dep = GU_DEP == 0 ? z : (GU_DEP == 1 ? pl : sq);
                        }
                        o[rr][i] = pack_bf16(hv[0], hv[1]);
                    }
                }
#pragma unroll
                for (int rr = 0; rr < 2; rr++) stg128(dst + j * 8192 + m * 4096 + rr * 512, o[rr]);
            }
            __syncwarp();
            if (lane == 0) mbar_arrive(bar(BAR_HST));
            TLC(42 + (u >> 1) * 3);
        }

        }

        CTA_COORDS;
        const bool leader = wg == lead_wg;
        float e[2][64];
        int s = leader ? 0 : NSOLO, pos = leader ? 0 : 2 * NSOLO % NBLK;
        uint32_t prev_bar = 0, prev_n = 0;
        auto step = [&](auto op, auto acc, int nblk, int boffs) {
            using Op = decltype(op);
            int pb = pos + boffs;
            if (pb >= NBLK) pb -= NBLK;
            const uint32_t da = make_desc(base, 16) + pos * (BLK >> 4), db = make_desc(base, Op::LBO) + pb * (BLK >> 4);
            mbar_wait(bar(BAR_FULL + (s & 7)), (s >> 3) & 1);
            TLP(8 + s - (leader ? 0 : NSOLO));
            mma_half<Op, decltype(acc)::value, 0>(e, da, db);
            if (decltype(acc)::value) {
                wgmma_wait<1>();
                if (lane == 0) mbar_arrive_n(prev_bar, prev_n);
            }
            prev_bar = bar(BAR_EMPTY + (s & 7));
            prev_n = 4 - nblk;
            pos += nblk;
            if (pos >= NBLK) pos -= NBLK;
            s++;
            mma_half<Op, 1, 1>(e, da, db);
        };
        const int bsh = leader ? 2 : 1;
        turn_wait(wg);
        step(OpDft(), IntC<0>(), leader ? 2 : 3, 1);
#pragma unroll 1
        for (int pass = 0; pass < 2; pass++) {
            const int solo_end = pass ? (leader ? nk : nk + NSOLO - NSPLIT) : NSOLO;
#pragma unroll 1
            while (s < solo_end) step(OpDft(), IntC<1>(), 2, 1);
            if (pass) break;
            if (leader) turn_give(wg ^ 1);
#pragma unroll 1
            while (s < ndft) step(OpDft(), IntC<1>(), 3, bsh);
#pragma unroll 1
            while (s < nk) step(OpDown(), IntC<1>(), 3, bsh);
        }

        const int ocol = nh * 256 + wg * 128, orow = rb * 128 + wq * 16;
        const uint32_t st_off = (wq * 16 + ((lane >> 3) & 1) * 8 + (lane & 7)) * 128;
        const uint32_t st_x = (lane >> 4), st_sw = lane & 7;
        const bool issuer = elect_one();
        uint32_t stg[2];
#pragma unroll
        for (int m = 0; m < 2; m++) {
            const int t = pos + NBLK - 2 + m;
            stg[m] = base + (t >= NBLK ? t - NBLK : t) * BLK;
        }
        auto stage = [&](int m, int i) {
            const float* v = e[m] + i * 8;
            stmatrix_x4(stg[m] + (i >> 2) * BOX_BYTES + st_off + ((((i & 3) * 2 + st_x) ^ st_sw) << 4), pack_out(v[0], v[1]),
                        pack_out(v[2], v[3]), pack_out(v[4], v[5]), pack_out(v[6], v[7]));
        };
        auto send = [&](int m, int h) {
            fence_async_smem();
            __syncwarp();
            if (issuer)
                tma_red_add_2d(&p.m[M_OUT], stg[m] + h * BOX_BYTES + wq * 2048, ocol + h * 64, orow + m * 64);
        };
        const uint32_t last_bar = prev_bar, last_par = ((s - 1) >> 3) & 1;
        if (leader) {
            wgmma_wait<0>();
            if (lane == 0) mbar_arrive_n(prev_bar, prev_n);
            TLC(50);
            mbar_wait(last_bar, last_par);
#pragma unroll
            for (int i = 0; i < 8; i++) {
                stage(0, i);
                if ((i & 3) == 3) send(0, i >> 2);
            }
        } else {
            static_assert(NSPLIT >= 4 && NSPLIT <= 5 && NSOLO >= 6 && NSOLO - NSPLIT <= 5, "the staging step must not be loaded again");
            uint32_t da[NSPLIT], db[NSPLIT];
#pragma unroll
            for (int j = 0; j < NSPLIT; j++) {
                int pa = pos + 2 * j + (j + NSOLO - NSPLIT >= 6 ? 2 : 0);
                if (pa >= NBLK) pa -= NBLK;
                const int pb = pa + 1 == NBLK ? 0 : pa + 1;
                da[j] = make_desc(base, 16) + pa * (BLK >> 4);
                db[j] = make_desc(base, OpDft::LBO) + pb * (BLK >> 4);
                mbar_wait(bar(BAR_FULL + ((s + j) & 7)), ((s + j) >> 3) & 1);
                wgmma_fence();
#pragma unroll
                for (int k = 0; k < 4; k++) wgmma_n128<1, 1, HI_128, HI_AB>(e[0], da[j] + 2 * k, db[j] + k * OpDft::BK);
                wgmma_commit();
                if (j == 0) {
                    wgmma_wait<1>();
                    if (lane == 0) mbar_arrive_n(prev_bar, prev_n);
                }
            }
            mbar_wait(last_bar, last_par);
#pragma unroll
            for (int j = 0; j < NSPLIT; j++) {
                wgmma_fence();
#pragma unroll
                for (int k = 0; k < 4; k++) {
                    wgmma_n128<1, 1, HI_128, HI_AB>(e[1], da[j] + OpDft::AM + 2 * k, db[j] + k * OpDft::BK);
                    if (j == 1 || j == 2) stage(0, (j - 1) * 4 + k);
                    if ((j == 2 || j == 3) && k == 1) send(0, j - 2);
                }
                wgmma_commit();
                if (j == 0) {
                    wgmma_wait<1>();
                    TLC(49);
                }
            }
            wgmma_wait<0>();
            TLC(50);
        }
#pragma unroll
        for (int i = 0; i < 8; i++) {
            stage(1, i);
            if ((i & 3) == 3) send(1, i >> 2);
        }
        if (issuer) {
            bulk_commit();
            TLC(51);
            bulk_wait_read<0>();
            TLC(52);
            mbar_arrive(bar(BAR_DONE));
        }
    }
}

typedef CUresult (*EncodeFn)(CUtensorMap*, CUtensorMapDataType, cuuint32_t, void*, const cuuint64_t*, const cuuint64_t*,
                             const cuuint32_t*, const cuuint32_t*, CUtensorMapInterleave, CUtensorMapSwizzle,
                             CUtensorMapL2promotion, CUtensorMapFloatOOBfill);

void map_2d(EncodeFn enc, CUtensorMap* m, const void* ptr, uint64_t rows, uint64_t cols, uint32_t box_rows) {
    cuuint64_t dims[2] = {cols, rows};
    cuuint64_t strides[1] = {cols * 2};
    cuuint32_t box[2] = {64, box_rows};
    cuuint32_t es[2] = {1, 1};
    enc(m, CU_TENSOR_MAP_DATA_TYPE_BFLOAT16, 2, const_cast<void*>(ptr), dims, strides, box, es, CU_TENSOR_MAP_INTERLEAVE_NONE,
        CU_TENSOR_MAP_SWIZZLE_128B, PROMO, CU_TENSOR_MAP_FLOAT_OOB_FILL_NONE);
}

void map_5d(EncodeFn enc, CUtensorMap* m, const void* ptr, uint64_t rows, uint64_t sa, uint64_t sb, uint32_t ngroups) {
    const cuuint64_t pitch = D_ * 2;
    cuuint64_t dims[5] = {D_, 2, 4, 4, rows / 32};
    cuuint64_t strides[4] = {pitch, sa * pitch, sb * pitch, 32 * pitch};
    cuuint32_t box[5] = {64, 2, 4, 4, ngroups};
    cuuint32_t es[5] = {1, 1, 1, 1, 1};
    enc(m, CU_TENSOR_MAP_DATA_TYPE_BFLOAT16, 5, const_cast<void*>(ptr), dims, strides, box, es, CU_TENSOR_MAP_INTERLEAVE_NONE,
        CU_TENSOR_MAP_SWIZZLE_128B, PROMO, CU_TENSOR_MAP_FLOAT_OOB_FILL_NONE);
}

}

extern "C" void kernel_launch(void* const* d_in, const int* in_sizes, int n_in, void* d_out, int out_size) {
    (void)in_sizes; (void)n_in; (void)out_size;
    void* fn = nullptr;
    cudaDriverEntryPointQueryResult qr;
    cudaGetDriverEntryPoint("cuTensorMapEncodeTiled", &fn, cudaEnableDefault, &qr);
    EncodeFn enc = (EncodeFn)fn;

    Params p;
    p.x = (const __nv_bfloat16*)d_in[0];
    p.wr = (const __nv_bfloat16*)d_in[3];
    p.wi = (const __nv_bfloat16*)d_in[4];
    p.wg = (const __nv_bfloat16*)d_in[6];
    p.wu = (const __nv_bfloat16*)d_in[7];
    p.wd = (const __nv_bfloat16*)d_in[8];
    p.zero = 0;
    map_2d(enc, &p.m[M_X], d_in[0], S_, D_, 128);
    map_5d(enc, &p.m[M_WR], d_in[3], D_, 8, 2, 4);
    map_5d(enc, &p.m[M_WI], d_in[4], D_, 8, 2, 4);
    map_2d(enc, &p.m[M_WG], d_in[6], D_, F_, 64);
    map_2d(enc, &p.m[M_WU], d_in[7], D_, F_, 64);
    map_2d(enc, &p.m[M_CR], d_in[1], S_, S_, 128);
    map_2d(enc, &p.m[M_CI], d_in[2], S_, S_, 128);
    map_5d(enc, &p.m[M_WD], d_in[8], F_, 8, 2, 2);
    map_2d(enc, &p.m[M_OUTI], d_out, S_, D_, 64);
    map_2d(enc, &p.m[M_OUT], d_out, S_, D_, 16);

    cudaFuncSetAttribute(fused_kernel, cudaFuncAttributeMaxDynamicSharedMemorySize, SMEM_BYTES);
    fused_kernel<<<NCTA, 384, SMEM_BYTES, cudaStreamPerThread>>>(p);
}
```
